```python
import torch

def _softmax(x, axis=-1):
    return torch.softmax(x, dim=axis)
def _gelu(x):
    return torch.nn.functional.gelu(x, approximate="tanh")
def _silu(x):
    return torch.nn.functional.silu(x)
def _sigmoid(x):
    return torch.sigmoid(x)
def _layernorm(x, axis=-1, eps=1e-5):
    m = x.mean(dim=axis, keepdim=True)
    v = x.var(dim=axis, keepdim=True, unbiased=False)
    return (x - m) / torch.sqrt(v + eps)
def _scatter_add(tgt, idx, src, axis=0):
    return tgt.clone().index_add_(axis, idx, src)
def _segment_sum(src, seg, n):
    out = torch.zeros((n,) + src.shape[1:], dtype=src.dtype)
    return out.index_add_(0, seg, src)
def _pad(x, pw):
    flat = tuple(v for pair in reversed(pw) for v in pair)
    return torch.nn.functional.pad(x, flat)

kernel_name = 'standalone__gqa_softmax__near_ridge'

def setup_inputs():

    _w = (lambda a: (lambda t: t.to(torch.bfloat16) if t.is_floating_point() else t)(torch.as_tensor(a)))
    B, Hq, Hkv, Sq, Sk, D = 16, 32, 16, 512, 512, 128
    return {
        "q": _w((lambda *s: torch.randn(*s, dtype=torch.bfloat16) * 0.8)(B, Hq, Sq, D)),
        "k": _w((lambda *s: torch.randn(*s, dtype=torch.bfloat16) * 0.8)(B, Hkv, Sk, D)),
        "v": _w((lambda *s: torch.randn(*s, dtype=torch.bfloat16) * 0.05)(B, Hkv, Sk, D)),
    }

def reference(q, k, v):
    B, Hq, Sq, D = q.shape
    Hkv = k.shape[1]
    rep = Hq // Hkv
    k = (lambda x, n, axis: torch.repeat_interleave(x, n, dim=axis))(k, rep, axis=1)
    v = (lambda x, n, axis: torch.repeat_interleave(x, n, dim=axis))(v, rep, axis=1)
    scale = D ** -0.5
    scores = torch.einsum("bhqd,bhkd->bhqk", q, k) * scale
    p = _softmax(scores, axis=-1)
    return torch.einsum("bhqk,bhkd->bhqd", p, v)
```

```cpp
#include <cuda_runtime.h>
#include <cuda_bf16.h>
#include <cuda.h>
#include <stdint.h>

namespace {

constexpr int kD = 128;
constexpr int kSeq = 512;
constexpr int kBatch = 16;
constexpr int kHq = 32;
constexpr int kHkv = 16;
constexpr int kNumCtas = 128;
constexpr int kHeadsPerCta = (kBatch * kHq) / kNumCtas;
constexpr int kTilesPerCta = kHeadsPerCta * 4;
constexpr int kStepsPerCta = kTilesPerCta * 4;
constexpr int kLoadsPerCta = kHeadsPerCta * 7;

constexpr uint32_t SM_K = 0;
constexpr uint32_t SM_V = 98304;
constexpr uint32_t SM_QO = 196608;
constexpr uint32_t SM_BAR = 229376;
constexpr uint32_t SMEM_BYTES = SM_BAR + 256 + 1024;

constexpr uint32_t B_FULLK = 0;
constexpr uint32_t B_EMPTYK = 32;
constexpr uint32_t B_FULLV = 64;
constexpr uint32_t B_EMPTYV = 96;
constexpr uint32_t B_FULLQ = 128;
constexpr uint32_t B_RDYO = 144;

#define SPIN_LIMIT 4000000

__device__ __forceinline__ void mbar_init(uint32_t bar, uint32_t cnt) {
  asm volatile("mbarrier.init.shared::cta.b64 [%0], %1;" ::"r"(bar), "r"(cnt) : "memory");
}
__device__ __forceinline__ void mbar_arrive(uint32_t bar) {
  asm volatile("mbarrier.arrive.shared::cta.b64 _, [%0];" ::"r"(bar) : "memory");
}
__device__ __forceinline__ void mbar_expect_tx(uint32_t bar, uint32_t bytes) {
  asm volatile("mbarrier.arrive.expect_tx.shared::cta.b64 _, [%0], %1;" ::"r"(bar), "r"(bytes) : "memory");
}
__device__ __forceinline__ void mbar_wait(uint32_t bar, uint32_t parity) {
  asm volatile(
      "{\n"
      ".reg .pred p;\n"
      ".reg .u32 c;\n"
      "mbarrier.try_wait.parity.shared::cta.b64 p, [%0], %1;\n"
      "@p bra DONE;\n"
      "mov.u32 c, 0;\n"
      "LOOP:\n"
      "mbarrier.try_wait.parity.shared::cta.b64 p, [%0], %1;\n"
      "@p bra DONE;\n"
      "add.u32 c, c, 1;\n"
      "setp.lt.u32 p, c, %2;\n"
      "@p bra LOOP;\n"
      "trap;\n"
      "DONE:\n"
      "}\n" ::"r"(bar), "r"(parity), "n"(SPIN_LIMIT) : "memory");
}
__device__ __forceinline__ void tma_load3(uint32_t dst, const CUtensorMap* tm, uint32_t bar, int row) {
  asm volatile(
      "cp.async.bulk.tensor.3d.shared::cluster.global.mbarrier::complete_tx::bytes [%0], [%1, {%3, %4, %3}], [%2];" ::"r"(dst),
      "l"(tm), "r"(bar), "r"(0), "r"(row)
      : "memory");
}
__device__ __forceinline__ void tma_store3(uint32_t src, const CUtensorMap* tm, int row) {
  asm volatile("cp.async.bulk.tensor.3d.global.shared::cta.bulk_group [%1, {%2, %3, %2}], [%0];" ::"r"(src), "l"(tm), "r"(0),
               "r"(row)
               : "memory");
}
__device__ __forceinline__ void l2_prefetch(const void* p, uint32_t bytes) {
  asm volatile("cp.async.bulk.prefetch.L2.global [%0], %1;" ::"l"(p), "r"(bytes) : "memory");
}

#define R8(a, i) "+f"(a[i + 0]), "+f"(a[i + 1]), "+f"(a[i + 2]), "+f"(a[i + 3]), "+f"(a[i + 4]), "+f"(a[i + 5]), "+f"(a[i + 6]), "+f"(a[i + 7])
#define ACC64(a) R8(a, 0), R8(a, 8), R8(a, 16), R8(a, 24), R8(a, 32), R8(a, 40), R8(a, 48), R8(a, 56)
#define W8(a, i) "=f"(a[i + 0]), "=f"(a[i + 1]), "=f"(a[i + 2]), "=f"(a[i + 3]), "=f"(a[i + 4]), "=f"(a[i + 5]), "=f"(a[i + 6]), "=f"(a[i + 7])
#define OUT64(a) W8(a, 0), W8(a, 8), W8(a, 16), W8(a, 24), W8(a, 32), W8(a, 40), W8(a, 48), W8(a, 56)
#define D64                                                                                                      \
  "{%0,%1,%2,%3,%4,%5,%6,%7,%8,%9,%10,%11,%12,%13,%14,%15,%16,%17,%18,%19,%20,%21,%22,%23,%24,%25,%26,%27,%28,"  \
  "%29,%30,%31,%32,%33,%34,%35,%36,%37,%38,%39,%40,%41,%42,%43,%44,%45,%46,%47,%48,%49,%50,%51,%52,%53,%54,%55," \
  "%56,%57,%58,%59,%60,%61,%62,%63}"

template <int TB>
__device__ __forceinline__ void wgmma_rs(float (&d)[64], const uint32_t* a, uint64_t db, int scale_d) {
  asm volatile(
      "{\n.reg .pred p;\nsetp.ne.b32 p, %69, 0;\n"
      "wgmma.mma_async.sync.aligned.m64n128k16.f32.bf16.bf16 " D64 ", {%64,%65,%66,%67}, %68, p, 1, 1, %70;\n}\n"
      : ACC64(d)
      : "r"(a[0]), "r"(a[1]), "r"(a[2]), "r"(a[3]), "l"(db), "r"(scale_d), "n"(TB));
}
template <int TB>
__device__ __forceinline__ void wgmma_rs_zero(float (&d)[64], const uint32_t* a, uint64_t db) {
  asm volatile(
      "{\n.reg .pred p;\nsetp.ne.b32 p, 0, 0;\n"
      "wgmma.mma_async.sync.aligned.m64n128k16.f32.bf16.bf16 " D64 ", {%64,%65,%66,%67}, %68, p, 1, 1, %69;\n}\n"
      : OUT64(d)
      : "r"(a[0]), "r"(a[1]), "r"(a[2]), "r"(a[3]), "l"(db), "n"(TB));
}
__device__ __forceinline__ void wg_fence() { asm volatile("wgmma.fence.sync.aligned;" ::: "memory"); }
__device__ __forceinline__ void wg_commit() { asm volatile("wgmma.commit_group.sync.aligned;" ::: "memory"); }
template <int N>
__device__ __forceinline__ void wg_wait() {
  asm volatile("wgmma.wait_group.sync.aligned %0;" ::"n"(N) : "memory");
}
__device__ __forceinline__ void fence_regs(float (&d)[64]) {
#pragma unroll
  for (int i = 0; i < 64; i++) asm volatile("" : "+f"(d[i])::"memory");
}
__device__ __forceinline__ void fence_regs(uint32_t (&d)[32]) {
#pragma unroll
  for (int i = 0; i < 32; i++) asm volatile("" : "+r"(d[i])::"memory");
}
__device__ __forceinline__ uint64_t mkdesc(uint32_t addr, uint32_t lbo, uint32_t sbo) {
  return (uint64_t)((addr & 0x3FFFF) >> 4) | ((uint64_t)(lbo >> 4) << 16) | ((uint64_t)(sbo >> 4) << 32) | (1ull << 62);
}
__device__ __forceinline__ float ex2(float x) {
  float y;
  asm("ex2.approx.ftz.f32 %0, %1;" : "=f"(y) : "f"(x));
  return y;
}
__device__ __forceinline__ uint32_t pack_bf16(float lo, float hi) {
  uint32_t r;
  asm("cvt.rn.bf16x2.f32 %0, %1, %2;" : "=r"(r) : "f"(hi), "f"(lo));
  return r;
}
__device__ __forceinline__ void ldsm4(uint32_t* r, uint32_t addr) {
  asm volatile("ldmatrix.sync.aligned.m8n8.x4.shared.b16 {%0,%1,%2,%3}, [%4];"
               : "=r"(r[0]), "=r"(r[1]), "=r"(r[2]), "=r"(r[3])
               : "r"(addr)
               : "memory");
}
__device__ __forceinline__ void stsm4(uint32_t addr, uint32_t r0, uint32_t r1, uint32_t r2, uint32_t r3) {
  asm volatile("stmatrix.sync.aligned.m8n8.x4.shared.b16 [%0], {%1,%2,%3,%4};" ::"r"(addr), "r"(r0), "r"(r1), "r"(r2), "r"(r3)
               : "memory");
}
__device__ __forceinline__ void bar_sync(int id) { asm volatile("bar.sync %0, 256;" ::"r"(id) : "memory"); }
__device__ __forceinline__ void bar_arrive(int id) { asm volatile("bar.arrive %0, 256;" ::"r"(id) : "memory"); }

__device__ __forceinline__ uint32_t slot_of_step(int i) {
  const uint32_t role = (0x01200210u >> ((i & 7) * 4)) & 3u;
  return (i & 16) ? (2u - role) : role;
}
constexpr uint32_t kWaitMask = 0x888Fu;
constexpr uint32_t kRelMask = 0xF111u;

__device__ __forceinline__ void issue_qk(float (&S)[64], const uint32_t (&Q)[32], uint32_t kaddr) {
  const uint64_t d0 = mkdesc(kaddr, 16, 1024);
  wgmma_rs_zero<0>(S, &Q[0], d0);
#pragma unroll
  for (int kk = 1; kk < 8; kk++) wgmma_rs<0>(S, &Q[4 * kk], d0 + (((kk / 4) * 16384 + (kk % 4) * 32) >> 4), 1);
  wg_commit();
}
__device__ __forceinline__ void issue_pv(float (&O)[64], const uint32_t (&P)[32], uint32_t vaddr, int accum) {
  const uint64_t d0 = mkdesc(vaddr, 16384, 1024);
  wgmma_rs<1>(O, &P[0], d0, accum);
#pragma unroll
  for (int kk = 1; kk < 8; kk++) wgmma_rs<1>(O, &P[4 * kk], d0 + ((kk * 2048) >> 4), 1);
  wg_commit();
}

__device__ __forceinline__ void softmax_block(float (&S)[64], float& m0, float& m1, float& l0, float& l1, float& a0, float& a1) {
  constexpr float c = 0.08838834764831845f * 1.4426950408889634f;
  float x0[4], x1[4];
#pragma unroll
  for (int j = 0; j < 4; j++) {
    x0[j] = fmaxf(S[4 * j], S[4 * j + 1]);
    x1[j] = fmaxf(S[4 * j + 2], S[4 * j + 3]);
  }
#pragma unroll
  for (int j = 4; j < 16; j++) {
    x0[j & 3] = fmaxf(x0[j & 3], S[4 * j]);
    x1[j & 3] = fmaxf(x1[j & 3], S[4 * j + 2]);
    x0[j & 3] = fmaxf(x0[j & 3], S[4 * j + 1]);
    x1[j & 3] = fmaxf(x1[j & 3], S[4 * j + 3]);
  }
  float y0 = fmaxf(fmaxf(x0[0], x0[1]), fmaxf(x0[2], x0[3]));
  float y1 = fmaxf(fmaxf(x1[0], x1[1]), fmaxf(x1[2], x1[3]));
  y0 = fmaxf(y0, __shfl_xor_sync(0xffffffffu, y0, 1));
  y1 = fmaxf(y1, __shfl_xor_sync(0xffffffffu, y1, 1));
  y0 = fmaxf(y0, __shfl_xor_sync(0xffffffffu, y0, 2));
  y1 = fmaxf(y1, __shfl_xor_sync(0xffffffffu, y1, 2));
  const float n0 = fmaxf(m0, y0 * c), n1 = fmaxf(m1, y1 * c);
  a0 = ex2(m0 - n0);
  a1 = ex2(m1 - n1);
  m0 = n0;
  m1 = n1;
  float s0[2] = {l0 * a0, 0.f}, s1[2] = {l1 * a1, 0.f};
#pragma unroll
  for (int j = 0; j < 16; j++) {
    S[4 * j + 0] = ex2(fmaf(S[4 * j + 0], c, -n0));
    S[4 * j + 1] = ex2(fmaf(S[4 * j + 1], c, -n0));
    S[4 * j + 2] = ex2(fmaf(S[4 * j + 2], c, -n1));
    S[4 * j + 3] = ex2(fmaf(S[4 * j + 3], c, -n1));
    s0[0] += S[4 * j + 0];
    s0[1] += S[4 * j + 1];
    s1[0] += S[4 * j + 2];
    s1[1] += S[4 * j + 3];
  }
  l0 = s0[0] + s0[1];
  l1 = s1[0] + s1[1];
}

__device__ __forceinline__ void load_q(uint32_t (&Q)[32], uint32_t qaddr) {
#pragma unroll
  for (int kk = 0; kk < 8; kk++) ldsm4(&Q[4 * kk], (qaddr ^ ((kk % 4) * 32)) + (kk / 4) * 8192);
}

__device__ __forceinline__ void epilogue(float (&O)[64], float l0, float l1, uint32_t qaddr, uint32_t bar, int lane) {
  l0 += __shfl_xor_sync(0xffffffffu, l0, 1);
  l1 += __shfl_xor_sync(0xffffffffu, l1, 1);
  l0 += __shfl_xor_sync(0xffffffffu, l0, 2);
  l1 += __shfl_xor_sync(0xffffffffu, l1, 2);
  const float i0 = __fdividef(1.f, l0), i1 = __fdividef(1.f, l1);
#pragma unroll
  for (int kk = 0; kk < 8; kk++) {
    const uint32_t r0 = pack_bf16(O[8 * kk + 0] * i0, O[8 * kk + 1] * i0);
    const uint32_t r1 = pack_bf16(O[8 * kk + 2] * i1, O[8 * kk + 3] * i1);
    const uint32_t r2 = pack_bf16(O[8 * kk + 4] * i0, O[8 * kk + 5] * i0);
    const uint32_t r3 = pack_bf16(O[8 * kk + 6] * i1, O[8 * kk + 7] * i1);
    stsm4((qaddr ^ ((kk % 4) * 32)) + (kk / 4) * 8192, r0, r1, r2, r3);
  }
  asm volatile("fence.proxy.async.shared::cta;" ::: "memory");
  __syncwarp();
  if (lane == 0) mbar_arrive(bar);
}

__global__ void __launch_bounds__(384, 1)
gqa_attn_kernel(const __grid_constant__ CUtensorMap tmQ, const __grid_constant__ CUtensorMap tmK,
                const __grid_constant__ CUtensorMap tmV, const __grid_constant__ CUtensorMap tmO) {
  extern __shared__ __align__(1024) uint8_t smem_raw[];
  const uint32_t sb = ((uint32_t)__cvta_generic_to_shared(smem_raw) + 1023u) & ~1023u;
  const uint32_t bars = sb + SM_BAR;
  const int warp = __shfl_sync(0xffffffffu, (int)(threadIdx.x >> 5), 0);
  const int lane = threadIdx.x & 31;
  const int pair = blockIdx.x >> 1, par = blockIdx.x & 1;

  if (threadIdx.x == 0) {
#pragma unroll
    for (int i = 0; i < 4; i++) {
      mbar_init(bars + B_FULLK + 8 * i, 1);
      mbar_init(bars + B_EMPTYK + 8 * i, 8);
      mbar_init(bars + B_FULLV + 8 * i, 1);
      mbar_init(bars + B_EMPTYV + 8 * i, 8);
    }
    mbar_init(bars + B_FULLQ, 1);
    mbar_init(bars + B_FULLQ + 8, 1);
    mbar_init(bars + B_RDYO, 4);
    mbar_init(bars + B_RDYO + 8, 4);
    asm volatile("fence.mbarrier_init.release.cluster;" ::: "memory");
    asm volatile("fence.proxy.async.shared::cta;" ::: "memory");
  }
  __syncthreads();

  if (warp >= 8) {
    asm volatile("setmaxnreg.dec.sync.aligned.u32 24;");
    if (lane == 0) {
      if (warp < 10) {
        const CUtensorMap* tm = (warp == 8) ? &tmK : &tmV;
        const uint32_t sbase = sb + ((warp == 8) ? SM_K : SM_V);
        const uint32_t bfull = bars + ((warp == 8) ? B_FULLK : B_FULLV);
        const uint32_t bempty = bfull + 32;
        int n = 0;
#pragma unroll 1
        for (int hh = 0; hh < kHeadsPerCta; hh++) {
          const int g = hh * (kNumCtas / 2) + pair;
#pragma unroll 1
          for (int j = 0; j < 7; j++, n++) {
            const int blk = (0x0303210 >> (4 * j)) & 3;
            const uint32_t role = (0x0000210 >> (4 * j)) & 3;
            const uint32_t slot = (hh & 1) ? 2u - role : role;
            if (n >= 3) mbar_wait(bempty + 8 * ((n - 3) & 3), ((n - 3) >> 2) & 1);
            mbar_expect_tx(bfull + 8 * (n & 3), 32768);
            tma_load3(sbase + slot * 32768, tm, bfull + 8 * (n & 3), g * kSeq + blk * 128);
          }
        }
      } else {
        const int w = warp - 10;
        const uint32_t buf = sb + SM_QO + w * 16384;
        const uint32_t bq = bars + B_FULLQ + 8 * w, bo = bars + B_RDYO + 8 * w;
        auto qrow = [&](int t) { return ((((t >> 2) * (kNumCtas / 2) + pair) * 2 + par) * 4 + (t & 3)) * 128 + w * 64; };
        mbar_expect_tx(bq, 16384);
        tma_load3(buf, &tmQ, bq, qrow(0));
        mbar_wait(bo, 0);
        mbar_expect_tx(bq, 16384);
        tma_load3(buf, &tmQ, bq, qrow(1));
#pragma unroll 1
        for (int t = 0; t < kTilesPerCta; t++) {
          mbar_wait(bo, (t + 1) & 1);
          tma_store3(buf, &tmO, qrow(t));
          asm volatile("cp.async.bulk.commit_group;" ::: "memory");
          asm volatile("cp.async.bulk.wait_group.read 0;" ::: "memory");
          if (t + 2 < kTilesPerCta) {
            mbar_expect_tx(bq, 16384);
            tma_load3(buf, &tmQ, bq, qrow(t + 2));
          } else {
            mbar_arrive(bq);
          }
        }
        asm volatile("cp.async.bulk.wait_group 0;" ::: "memory");
      }
    }
  } else {
    asm volatile("setmaxnreg.inc.sync.aligned.u32 240;");
    const int wg = warp >> 2;
    const int my_bar = 1 + wg, other_bar = 2 - wg;
    const uint32_t bq = bars + B_FULLQ + 8 * wg, bo = bars + B_RDYO + 8 * wg;
    uint32_t qaddr;
    {
      const int row = (warp & 3) * 16 + (lane & 15);
      qaddr = sb + SM_QO + wg * 16384 + row * 128 + ((((uint32_t)lane >> 4) ^ (row & 7)) << 4);
    }
    float S[64], O[64];
    uint32_t P[32], Q[32];
    float m0 = -INFINITY, m1 = -INFINITY, l0 = 0.f, l1 = 0.f, a0, a1;
#pragma unroll
    for (int i = 0; i < 64; i++) O[i] = 0.f;

    if (wg == 1) bar_arrive(other_bar);

    mbar_wait(bq, 0);
    load_q(Q, qaddr);
    __syncwarp();
    if (lane == 0) mbar_arrive(bo);
    mbar_wait(bars + B_FULLK, 0);
    bar_sync(my_bar);
    wg_fence();
    issue_qk(S, Q, sb + SM_K);
    bar_arrive(other_bar);
    wg_wait<0>();
    fence_regs(S);
    if (lane == 0) mbar_arrive(bars + B_EMPTYK);
    softmax_block(S, m0, m1, l0, l1, a0, a1);
#pragma unroll
    for (int i = 0; i < 32; i++) P[i] = pack_bf16(S[2 * i], S[2 * i + 1]);

    int nk = 1, rk = 1, nv = 0, rv = 0;
    uint32_t vslot = 0;
#pragma unroll 1
    for (int i = 1; i < kStepsPerCta; i++) {
      const uint32_t kslot = slot_of_step(i);
      if ((kWaitMask >> (i & 15)) & 1) {
        mbar_wait(bars + B_FULLK + 8 * (nk & 3), (nk >> 2) & 1);
        nk++;
      }
      if ((kWaitMask >> ((i - 1) & 15)) & 1) {
        mbar_wait(bars + B_FULLV + 8 * (nv & 3), (nv >> 2) & 1);
        nv++;
      }
      bar_sync(my_bar);
      fence_regs(O);
      wg_fence();
      issue_qk(S, Q, sb + SM_K + kslot * 32768);
      issue_pv(O, P, sb + SM_V + vslot * 32768, (i - 1) & 3);
      bar_arrive(other_bar);
      wg_wait<1>();
      fence_regs(S);
      const float lf0 = l0, lf1 = l1;
      if ((i & 3) == 0) {
        m0 = -INFINITY;
        m1 = -INFINITY;
      }
      softmax_block(S, m0, m1, l0, l1, a0, a1);
      fence_regs(S);
      if ((kRelMask >> (i & 15)) & 1) {
        if (lane == 0) mbar_arrive(bars + B_EMPTYK + 8 * (rk & 3));
        rk++;
      }
      wg_wait<0>();
      fence_regs(O);
      fence_regs(P);
      fence_regs(S);
      if ((kRelMask >> ((i - 1) & 15)) & 1) {
        if (lane == 0) mbar_arrive(bars + B_EMPTYV + 8 * (rv & 3));
        rv++;
      }
      if ((i & 3) == 0) {
        epilogue(O, lf0, lf1, qaddr, bo, lane);
      } else {
#pragma unroll
        for (int j = 0; j < 16; j++) {
          O[4 * j + 0] *= a0;
          O[4 * j + 1] *= a0;
          O[4 * j + 2] *= a1;
          O[4 * j + 3] *= a1;
        }
      }
#pragma unroll
      for (int j = 0; j < 32; j++) P[j] = pack_bf16(S[2 * j], S[2 * j + 1]);
      if ((i & 3) == 3) {
        mbar_wait(bq, ((i >> 2) + 1) & 1);
        load_q(Q, qaddr);
      }
      vslot = kslot;
    }
    mbar_wait(bars + B_FULLV + 8 * (nv & 3), (nv >> 2) & 1);
    bar_sync(my_bar);
    fence_regs(O);
    wg_fence();
    issue_pv(O, P, sb + SM_V + vslot * 32768, 1);
    if (wg == 0) bar_arrive(other_bar);
    wg_wait<0>();
    fence_regs(O);
    epilogue(O, l0, l1, qaddr, bo, lane);
  }
}

typedef CUresult (*EncodeTiledFn)(CUtensorMap*, CUtensorMapDataType, cuuint32_t, void*, const cuuint64_t*, const cuuint64_t*,
                                  const cuuint32_t*, const cuuint32_t*, CUtensorMapInterleave, CUtensorMapSwizzle,
                                  CUtensorMapL2promotion, CUtensorMapFloatOOBfill);

void make_map(EncodeTiledFn fn, CUtensorMap* tm, const void* ptr, uint64_t rows, uint32_t box_rows) {
  cuuint64_t dims[3] = {64, rows, 2};
  cuuint64_t strides[2] = {256, 128};
  cuuint32_t box[3] = {64, box_rows, 2};
  cuuint32_t estr[3] = {1, 1, 1};
  fn(tm, CU_TENSOR_MAP_DATA_TYPE_BFLOAT16, 3, const_cast<void*>(ptr), dims, strides, box, estr, CU_TENSOR_MAP_INTERLEAVE_NONE,
     CU_TENSOR_MAP_SWIZZLE_128B, CU_TENSOR_MAP_L2_PROMOTION_L2_256B, CU_TENSOR_MAP_FLOAT_OOB_FILL_NONE);
}

}

extern "C" void kernel_launch(void* const* d_in, const int* in_sizes, int n_in, void* d_out, int out_size) {
  (void)in_sizes;
  (void)n_in;
  (void)out_size;
  static EncodeTiledFn fn = nullptr;
  if (!fn) {
    void* p = nullptr;
    cudaDriverEntryPointQueryResult qr;
    cudaGetDriverEntryPoint("cuTensorMapEncodeTiled", &p, cudaEnableDefault, &qr);
    fn = (EncodeTiledFn)p;
    cudaFuncSetAttribute(gqa_attn_kernel, cudaFuncAttributeMaxDynamicSharedMemorySize, SMEM_BYTES);
  }
  CUtensorMap tmQ, tmK, tmV, tmO;
  make_map(fn, &tmQ, d_in[0], (uint64_t)kBatch * kHq * kSeq, 64);
  make_map(fn, &tmK, d_in[1], (uint64_t)kBatch * kHkv * kSeq, 128);
  make_map(fn, &tmV, d_in[2], (uint64_t)kBatch * kHkv * kSeq, 128);
  make_map(fn, &tmO, d_out, (uint64_t)kBatch * kHq * kSeq, 64);
  gqa_attn_kernel<<<kNumCtas, 384, SMEM_BYTES>>>(tmQ, tmK, tmV, tmO);
}
```

```cpp
#include <cuda_runtime.h>
#include <cuda_bf16.h>
#include <cuda.h>
#include <stdint.h>

namespace {

constexpr int kD = 128;
constexpr int kSeq = 512;
constexpr int kBatch = 16;
constexpr int kHq = 32;
constexpr int kHkv = 16;
constexpr int kNumCtas = 128;
constexpr int kHeadsPerCta = (kBatch * kHq) / kNumCtas;
constexpr int kTilesPerCta = kHeadsPerCta * 4;
constexpr int kStepsPerCta = kTilesPerCta * 4;
constexpr int kLoadsPerCta = kHeadsPerCta * 7;

constexpr uint32_t SM_K = 0;
constexpr uint32_t SM_V = 98304;
constexpr uint32_t SM_QO = 196608;
constexpr uint32_t SM_BAR = 229376;
constexpr uint32_t SMEM_BYTES = SM_BAR + 256 + 1024;

constexpr uint32_t B_FULLK = 0;
constexpr uint32_t B_EMPTYK = 32;
constexpr uint32_t B_FULLV = 64;
constexpr uint32_t B_EMPTYV = 96;
constexpr uint32_t B_FULLQ = 128;
constexpr uint32_t B_RDYO = 144;
constexpr uint32_t B_DONE = 160;
constexpr uint32_t B_FB = 176;
constexpr uint32_t B_FLAG = 192;

#define SPIN_LIMIT 4000000
#define HINT_Q
#define HINT_O
#define HINT_KV
#define PFD 3

#define TR(step, k)
#define TP(a, n)
#define TRW(step, k)
#define TRG(k)

__device__ __forceinline__ void mbar_init(uint32_t bar, uint32_t cnt) {
  asm volatile("mbarrier.init.shared::cta.b64 [%0], %1;" ::"r"(bar), "r"(cnt) : "memory");
}
__device__ __forceinline__ void mbar_arrive(uint32_t bar) {
  asm volatile("mbarrier.arrive.shared::cta.b64 _, [%0];" ::"r"(bar) : "memory");
}
__device__ __forceinline__ void mbar_expect_tx(uint32_t bar, uint32_t bytes) {
  asm volatile("mbarrier.arrive.expect_tx.shared::cta.b64 _, [%0], %1;" ::"r"(bar), "r"(bytes) : "memory");
}
__device__ __forceinline__ void mbar_wait(uint32_t bar, uint32_t parity) {
  asm volatile(
      "{\n"
      ".reg .pred p;\n"
      ".reg .u32 c;\n"
      "mbarrier.try_wait.parity.shared::cta.b64 p, [%0], %1;\n"
      "@p bra DONE;\n"
      "mov.u32 c, 0;\n"
      "LOOP:\n"
      "mbarrier.try_wait.parity.shared::cta.b64 p, [%0], %1;\n"
      "@p bra DONE;\n"
      "add.u32 c, c, 1;\n"
      "setp.lt.u32 p, c, %2;\n"
      "@p bra LOOP;\n"
      "trap;\n"
      "DONE:\n"
      "}\n" ::"r"(bar), "r"(parity), "n"(SPIN_LIMIT) : "memory");
}
__device__ __forceinline__ void tma_load3(uint32_t dst, const CUtensorMap* tm, uint32_t bar, int row) {
  asm volatile(
      "cp.async.bulk.tensor.3d.shared::cluster.global.mbarrier::complete_tx::bytes [%0], [%1, {%3, %4, %3}], [%2];" ::"r"(dst),
      "l"(tm), "r"(bar), "r"(0), "r"(row)
      : "memory");
}
__device__ __forceinline__ void tma_store3(uint32_t src, const CUtensorMap* tm, int row) {
  asm volatile("cp.async.bulk.tensor.3d.global.shared::cta.bulk_group [%1, {%2, %3, %2}], [%0];" ::"r"(src), "l"(tm), "r"(0),
               "r"(row)
               : "memory");
}
__device__ __forceinline__ void tma_load3_hint(uint32_t dst, const CUtensorMap* tm, uint32_t bar, int row, uint64_t pol) {
  asm volatile(
      "cp.async.bulk.tensor.3d.shared::cluster.global.mbarrier::complete_tx::bytes.L2::cache_hint [%0], [%1, {%3, %4, %3}], [%2], %5;" ::"r"(dst),
      "l"(tm), "r"(bar), "r"(0), "r"(row), "l"(pol)
      : "memory");
}
__device__ __forceinline__ void tma_store3_hint(uint32_t src, const CUtensorMap* tm, int row, uint64_t pol) {
  asm volatile("cp.async.bulk.tensor.3d.global.shared::cta.bulk_group.L2::cache_hint [%1, {%2, %3, %2}], [%0], %4;" ::"r"(src), "l"(tm), "r"(0),
               "r"(row), "l"(pol)
               : "memory");
}
__device__ __forceinline__ void tma_load3_mc(uint32_t dst, const CUtensorMap* tm, uint32_t bar, int row) {
  asm volatile(
      "cp.async.bulk.tensor.3d.shared::cluster.global.mbarrier::complete_tx::bytes.multicast::cluster [%0], [%1, {%3, %4, %3}], [%2], %5;" ::"r"(dst),
      "l"(tm), "r"(bar), "r"(0), "r"(row), "h"((uint16_t)3)
      : "memory");
}
__device__ __forceinline__ void tma_load3_mc_hint(uint32_t dst, const CUtensorMap* tm, uint32_t bar, int row, uint64_t pol) {
  asm volatile(
      "cp.async.bulk.tensor.3d.shared::cluster.global.mbarrier::complete_tx::bytes.multicast::cluster.L2::cache_hint [%0], [%1, {%3, %4, %3}], [%2], %5, %6;" ::"r"(dst),
      "l"(tm), "r"(bar), "r"(0), "r"(row), "h"((uint16_t)3), "l"(pol)
      : "memory");
}
__device__ __forceinline__ uint32_t mapa(uint32_t addr, uint32_t rank) {
  uint32_t r;
  asm("mapa.shared::cluster.u32 %0, %1, %2;" : "=r"(r) : "r"(addr), "r"(rank));
  return r;
}
__device__ __forceinline__ void mbar_arrive_cl(uint32_t bar) {
  asm volatile("mbarrier.arrive.shared::cluster.b64 _, [%0];" ::"r"(bar) : "memory");
}
__device__ __forceinline__ void mbar_expect_tx_cl(uint32_t bar, uint32_t bytes) {
  asm volatile("mbarrier.arrive.expect_tx.shared::cluster.b64 _, [%0], %1;" ::"r"(bar), "r"(bytes) : "memory");
}
__device__ __forceinline__ void cluster_arrive() { asm volatile("barrier.cluster.arrive.relaxed;" ::: "memory"); }
__device__ __forceinline__ void cluster_wait() { asm volatile("barrier.cluster.wait;" ::: "memory"); }
__device__ __forceinline__ uint64_t policy_evict_first() {
  uint64_t p;
  asm volatile("createpolicy.fractional.L2::evict_first.b64 %0, 1.0;" : "=l"(p));
  return p;
}
__device__ __forceinline__ void l2_prefetch(const void* p, uint32_t bytes) {
  asm volatile("cp.async.bulk.prefetch.L2.global [%0], %1;" ::"l"(p), "r"(bytes) : "memory");
}

#define R8(a, i) "+f"(a[i + 0]), "+f"(a[i + 1]), "+f"(a[i + 2]), "+f"(a[i + 3]), "+f"(a[i + 4]), "+f"(a[i + 5]), "+f"(a[i + 6]), "+f"(a[i + 7])
#define ACC64(a) R8(a, 0), R8(a, 8), R8(a, 16), R8(a, 24), R8(a, 32), R8(a, 40), R8(a, 48), R8(a, 56)
#define W8(a, i) "=f"(a[i + 0]), "=f"(a[i + 1]), "=f"(a[i + 2]), "=f"(a[i + 3]), "=f"(a[i + 4]), "=f"(a[i + 5]), "=f"(a[i + 6]), "=f"(a[i + 7])
#define OUT64(a) W8(a, 0), W8(a, 8), W8(a, 16), W8(a, 24), W8(a, 32), W8(a, 40), W8(a, 48), W8(a, 56)
#define D64                                                                                                      \
  "{%0,%1,%2,%3,%4,%5,%6,%7,%8,%9,%10,%11,%12,%13,%14,%15,%16,%17,%18,%19,%20,%21,%22,%23,%24,%25,%26,%27,%28,"  \
  "%29,%30,%31,%32,%33,%34,%35,%36,%37,%38,%39,%40,%41,%42,%43,%44,%45,%46,%47,%48,%49,%50,%51,%52,%53,%54,%55," \
  "%56,%57,%58,%59,%60,%61,%62,%63}"

template <int TB>
__device__ __forceinline__ void wgmma_rs(float (&d)[64], const uint32_t* a, uint64_t db, int scale_d) {
  asm volatile(
      "{\n.reg .pred p;\nsetp.ne.b32 p, %69, 0;\n"
      "wgmma.mma_async.sync.aligned.m64n128k16.f32.bf16.bf16 " D64 ", {%64,%65,%66,%67}, %68, p, 1, 1, %70;\n}\n"
      : ACC64(d)
      : "r"(a[0]), "r"(a[1]), "r"(a[2]), "r"(a[3]), "l"(db), "r"(scale_d), "n"(TB));
}
template <int TB>
__device__ __forceinline__ void wgmma_rs_zero(float (&d)[64], const uint32_t* a, uint64_t db) {
  asm volatile(
      "{\n.reg .pred p;\nsetp.ne.b32 p, 0, 0;\n"
      "wgmma.mma_async.sync.aligned.m64n128k16.f32.bf16.bf16 " D64 ", {%64,%65,%66,%67}, %68, p, 1, 1, %69;\n}\n"
      : OUT64(d)
      : "r"(a[0]), "r"(a[1]), "r"(a[2]), "r"(a[3]), "l"(db), "n"(TB));
}
__device__ __forceinline__ void wg_fence() { asm volatile("wgmma.fence.sync.aligned;" ::: "memory"); }
__device__ __forceinline__ void wg_commit() { asm volatile("wgmma.commit_group.sync.aligned;" ::: "memory"); }
template <int N>
__device__ __forceinline__ void wg_wait() {
  asm volatile("wgmma.wait_group.sync.aligned %0;" ::"n"(N) : "memory");
}
__device__ __forceinline__ void fence_regs(float (&d)[64]) {
#pragma unroll
  for (int i = 0; i < 64; i++) asm volatile("" : "+f"(d[i])::"memory");
}
__device__ __forceinline__ void fence_regs(uint32_t (&d)[32]) {
#pragma unroll
  for (int i = 0; i < 32; i++) asm volatile("" : "+r"(d[i])::"memory");
}
__device__ __forceinline__ uint64_t mkdesc(uint32_t addr, uint32_t lbo, uint32_t sbo) {
  return (uint64_t)((addr & 0x3FFFF) >> 4) | ((uint64_t)(lbo >> 4) << 16) | ((uint64_t)(sbo >> 4) << 32) | (1ull << 62);
}
__device__ __forceinline__ float ex2(float x) {
  float y;
  asm("ex2.approx.ftz.f32 %0, %1;" : "=f"(y) : "f"(x));
  return y;
}
__device__ __forceinline__ uint32_t pack_bf16(float lo, float hi) {
  uint32_t r;
  asm("cvt.rn.bf16x2.f32 %0, %1, %2;" : "=r"(r) : "f"(hi), "f"(lo));
  return r;
}
__device__ __forceinline__ void ldsm4(uint32_t* r, uint32_t addr) {
  asm volatile("ldmatrix.sync.aligned.m8n8.x4.shared.b16 {%0,%1,%2,%3}, [%4];"
               : "=r"(r[0]), "=r"(r[1]), "=r"(r[2]), "=r"(r[3])
               : "r"(addr)
               : "memory");
}
__device__ __forceinline__ void stsm4(uint32_t addr, uint32_t r0, uint32_t r1, uint32_t r2, uint32_t r3) {
  asm volatile("stmatrix.sync.aligned.m8n8.x4.shared.b16 [%0], {%1,%2,%3,%4};" ::"r"(addr), "r"(r0), "r"(r1), "r"(r2), "r"(r3)
               : "memory");
}
__device__ __forceinline__ void bar_sync(int id) { asm volatile("bar.sync %0, 256;" ::"r"(id) : "memory"); }
__device__ __forceinline__ void bar_arrive(int id) { asm volatile("bar.arrive %0, 256;" ::"r"(id) : "memory"); }

__device__ __forceinline__ uint64_t desc64(uint32_t lo) { return ((uint64_t)0x40000040u << 32) | lo; }

__device__ __forceinline__ void issue_qk(float (&S)[64], const uint32_t (&Q)[32], uint32_t dk) {
  const uint64_t d0 = desc64(dk & 0x7FFFFFFFu);
  wgmma_rs_zero<0>(S, &Q[0], d0);
#pragma unroll
  for (int kk = 1; kk < 8; kk++) wgmma_rs<0>(S, &Q[4 * kk], d0 + (((kk / 4) * 16384 + (kk % 4) * 32) >> 4), 1);
  wg_commit();
}
template <bool ZERO>
__device__ __forceinline__ void issue_pv(float (&O)[64], const uint32_t (&P)[32], uint32_t dv) {
  const uint64_t d0 = desc64(dv & 0x7FFFFFFFu);
  if (ZERO)
    wgmma_rs_zero<1>(O, &P[0], d0);
  else
    wgmma_rs<1>(O, &P[0], d0, 1);
#pragma unroll
  for (int kk = 1; kk < 8; kk++) wgmma_rs<1>(O, &P[4 * kk], d0 + ((kk * 2048) >> 4), 1);
  wg_commit();
}

template <int LO, int HI, bool INIT>
__device__ __forceinline__ void exp_part(float (&S)[64], float& l0, float& l1) {
#pragma unroll
  for (int j = LO; j < HI; j++) {
    S[j] = ex2(S[j]);
    if (INIT && j == 0)
      l0 = S[j];
    else if (INIT && j == 2)
      l1 = S[j];
    else if (j & 2)
      l1 += S[j];
    else
      l0 += S[j];
  }
}
__device__ __forceinline__ void mbar_arrive_anchor(uint32_t bar, uint32_t pred, float l0, float l1) {
  asm volatile(
      "{\n.reg .pred p, q;\n.reg .f32 n;\n"
      "setp.ne.u32 q, %1, 0;\n"
      "neg.f32 n, %3;\n"
      "setp.geu.and.f32 p, %2, n, q;\n"
      "@p mbarrier.arrive.shared::cluster.b64 _, [%0];\n}\n" ::"r"(bar),
      "r"(pred), "f"(l0), "f"(l1)
      : "memory");
}

template <bool SCALE>
__device__ __forceinline__ void load_q(uint32_t (&Q)[32], uint32_t qaddr) {
#pragma unroll
  for (int kk = 0; kk < 8; kk++) ldsm4(&Q[4 * kk], (qaddr ^ ((kk % 4) * 32)) + (kk / 4) * 8192);
  if (!SCALE) return;
#pragma unroll
  for (int j = 0; j < 32; j++)
    asm("{.reg .b32 t; mul.rn.bf16x2 t, %0, %1; fma.rn.bf16x2 %0, t, %2, t;}" : "+r"(Q[j]) : "r"(0x3E003E00u), "r"(0x3CA53CA5u));
}

template <bool CHECK>
__device__ __forceinline__ void epilogue(float (&O)[64], float l0, float l1, uint32_t qaddr, uint32_t flag) {
  l0 += __shfl_xor_sync(0xffffffffu, l0, 1);
  l1 += __shfl_xor_sync(0xffffffffu, l1, 1);
  l0 += __shfl_xor_sync(0xffffffffu, l0, 2);
  l1 += __shfl_xor_sync(0xffffffffu, l1, 2);
  if (CHECK) {
    constexpr uint32_t lo = (127u - 24u) << 23;
    const uint32_t bad = ((__float_as_uint(l0) - lo) | (__float_as_uint(l1) - lo)) & 0xE0000000u;
    asm volatile("{.reg .pred p; setp.ne.u32 p, %1, 0; @p st.shared.u8 [%0], %1;}" ::"r"(flag), "r"(bad >> 24) : "memory");
  }
  const float i0 = __fdividef(1.f, l0), i1 = __fdividef(1.f, l1);
#pragma unroll
  for (int kk = 0; kk < 8; kk++) {
    const uint32_t r0 = pack_bf16(O[8 * kk + 0] * i0, O[8 * kk + 1] * i0);
    const uint32_t r1 = pack_bf16(O[8 * kk + 2] * i1, O[8 * kk + 3] * i1);
    const uint32_t r2 = pack_bf16(O[8 * kk + 4] * i0, O[8 * kk + 5] * i0);
    const uint32_t r3 = pack_bf16(O[8 * kk + 6] * i1, O[8 * kk + 7] * i1);
    stsm4((qaddr ^ ((kk % 4) * 32)) + (kk / 4) * 8192, r0, r1, r2, r3);
  }
}

__device__ __forceinline__ void softmax_block(float (&S)[64], float& m0, float& m1, float& l0, float& l1, float& a0, float& a1) {
  constexpr float c = 0.08838834764831845f * 1.4426950408889634f;
  float y0 = fmaxf(S[0], S[1]), y1 = fmaxf(S[2], S[3]);
#pragma unroll
  for (int j = 1; j < 16; j++) {
    y0 = fmaxf(y0, fmaxf(S[4 * j], S[4 * j + 1]));
    y1 = fmaxf(y1, fmaxf(S[4 * j + 2], S[4 * j + 3]));
  }
  y0 = fmaxf(y0, __shfl_xor_sync(0xffffffffu, y0, 1));
  y1 = fmaxf(y1, __shfl_xor_sync(0xffffffffu, y1, 1));
  y0 = fmaxf(y0, __shfl_xor_sync(0xffffffffu, y0, 2));
  y1 = fmaxf(y1, __shfl_xor_sync(0xffffffffu, y1, 2));
  const float n0 = fmaxf(m0, y0 * c), n1 = fmaxf(m1, y1 * c);
  const float e0 = n0 == -INFINITY ? 0.f : n0, e1 = n1 == -INFINITY ? 0.f : n1;
  a0 = ex2(m0 - e0);
  a1 = ex2(m1 - e1);
  m0 = n0;
  m1 = n1;
  l0 *= a0;
  l1 *= a1;
#pragma unroll
  for (int j = 0; j < 16; j++) {
    S[4 * j + 0] = ex2(fmaf(S[4 * j + 0], c, -e0));
    S[4 * j + 1] = ex2(fmaf(S[4 * j + 1], c, -e0));
    S[4 * j + 2] = ex2(fmaf(S[4 * j + 2], c, -e1));
    S[4 * j + 3] = ex2(fmaf(S[4 * j + 3], c, -e1));
    l0 += S[4 * j + 0] + S[4 * j + 1];
    l1 += S[4 * j + 2] + S[4 * j + 3];
  }
}

__global__ void __cluster_dims__(2, 1, 1) __launch_bounds__(384, 1)
gqa_attn_kernel(const __grid_constant__ CUtensorMap tmQ, const __grid_constant__ CUtensorMap tmK,
                const __grid_constant__ CUtensorMap tmV, const __grid_constant__ CUtensorMap tmO,
                const uint8_t* __restrict__ gq, const uint8_t* __restrict__ gk, const uint8_t* __restrict__ gv) {
  extern __shared__ __align__(1024) uint8_t smem_raw[];
  const uint32_t sb = ((uint32_t)__cvta_generic_to_shared(smem_raw) + 1023u) & ~1023u;
  const uint32_t bars = sb + SM_BAR;
  const int warp = __shfl_sync(0xffffffffu, (int)(threadIdx.x >> 5), 0);
  const int lane = threadIdx.x & 31;
  const int par = blockIdx.x & 1, u = (blockIdx.x >> 1) & 1, pg = blockIdx.x >> 2;
#define OPAT 0x1210
  const int o0 = (OPAT >> (4 * (pg & 3))) & 3;
  const int v0 = u ? o0 : 4 - o0;
  auto head_of = [&](int seg) { return (seg == 0 ? 0 : seg == 4 ? 7 : 3 * u + seg) * 32 + pg; };

  auto qrow = [&](int t, int w) {
    const int v = v0 + t;
    return ((head_of(v >> 2) * 2 + par) * 4 + ((v & 3) ^ (3 * u))) * 128 + w * 64;
  };

  TRG(0);
  if (threadIdx.x == 0) {
#pragma unroll
    for (int i = 0; i < 3; i++) {
      mbar_init(bars + B_FULLK + 8 * i, 1);
      mbar_init(bars + B_EMPTYK + 8 * i, 16);
      mbar_init(bars + B_FULLV + 8 * i, 1);
      mbar_init(bars + B_EMPTYV + 8 * i, 16);
    }
    mbar_init(bars + B_FULLQ, 1);
    mbar_init(bars + B_FULLQ + 8, 1);
    mbar_init(bars + B_RDYO, 4);
    mbar_init(bars + B_RDYO + 8, 4);
    mbar_init(bars + B_DONE, 1);
    mbar_init(bars + B_DONE + 8, 1);
    mbar_init(bars + B_FB, 1);
    mbar_init(bars + B_FB + 8, 1);
    asm volatile("st.shared.v4.u32 [%0], {%1,%1,%1,%1};" ::"r"(bars + B_FLAG), "r"(0) : "memory");
    asm volatile("st.shared.v4.u32 [%0], {%1,%1,%1,%1};" ::"r"(bars + B_FLAG + 16), "r"(0) : "memory");
    asm volatile("fence.mbarrier_init.release.cluster;" ::: "memory");
    asm volatile("fence.proxy.async.shared::cta;" ::: "memory");
  }
  __syncwarp();
  cluster_arrive();
  cluster_wait();

  if (warp >= 8) {
    asm volatile("setmaxnreg.dec.sync.aligned.u32 24;");
    if (lane == 0) {
      if (warp == 8) {
        const CUtensorMap* tm = par ? &tmV : &tmK;
        const uint32_t sbase = sb + (par ? SM_V : SM_K);
        const uint32_t bfull = bars + (par ? B_FULLV : B_FULLK);
        const uint32_t bfull_peer = mapa(bfull, par ^ 1);
        const uint32_t bempty = bfull + 32;
        const uint8_t* gp = par ? gv : gk;
        const uint64_t pol = policy_evict_first();
        uint32_t X = 0, s1 = 1, s2 = 2, pe = 7;
        int v = v0, f = 4 * (v0 >> 2), n_ld = 0;
        const int f_end = 4 * ((v0 + 15) >> 2) + 3;
#pragma unroll 1
        while (v < v0 + kTilesPerCta) {
          const int seg = v >> 2, g = head_of(seg);
          const int n = min(4 - (v & 3), v0 + kTilesPerCta - v);
#pragma unroll 1
          for (int j = 0; j < n + 3; j++) {
            const int blk = j < 3 ? j : (j & 1) * 3;
            const uint32_t slot = j == 1 ? s1 : j == 2 ? s2 : X;
            mbar_wait(bempty + 8 * slot, (pe >> slot) & 1);
            pe ^= 1u << slot;
            TP(0, n_ld);
            n_ld++;
            mbar_expect_tx(bfull + 8 * slot, 32768);
            mbar_expect_tx_cl(bfull_peer + 8 * slot, 32768);
            if (n == 4 && ((0x66 >> j) & 1))
              tma_load3_mc_hint(sbase + slot * 32768, tm, bfull + 8 * slot, g * kSeq + blk * 128, pol);
            else
              tma_load3_mc(sbase + slot * 32768, tm, bfull + 8 * slot, g * kSeq + blk * 128);
            f = max(f, 4 * seg + min(j, 3));
            const int jj = PFD - (n + 2 - j) - 1;
            int fm = jj >= 0 ? 4 * seg + 4 + min(jj, 3) : 4 * seg + min(j + PFD, 3);
            if (v == v0 && j < 3) fm = 4 * seg + (j == 2 ? 3 : 0);
            fm = min(fm, f_end);
#pragma unroll 1
            while (f < fm) {
              f++;
              l2_prefetch(gp + (size_t)(head_of(f >> 2) * kSeq + (f & 3) * 128) * 256, 32768);
            }
          }
          const uint32_t a = (n & 1) ? s1 : s2, b = (n & 1) ? s2 : s1;
          s1 = b;
          s2 = X;
          X = a;
          v += n;
        }
      } else if (warp >= 10) {
        const int w = warp - 10;
        const uint32_t buf = sb + SM_QO + w * 16384;
        const uint32_t bq = bars + B_FULLQ + 8 * w, bo = bars + B_RDYO + 8 * w;
        const uint64_t pol = policy_evict_first();
#define QLOAD(t) tma_load3_hint(buf, &tmQ, bq, qrow(t, w), pol)
#define OSTORE(t) tma_store3_hint(buf, &tmO, qrow(t, w), pol)
        mbar_expect_tx(bq, 16384);
        QLOAD(0);
        mbar_wait(bo, 0);
        mbar_expect_tx(bq, 16384);
        QLOAD(1);
#pragma unroll 1
        for (int t = 0; t < kTilesPerCta; t++) {
          mbar_wait(bo, (t + 1) & 1);
          TP(2 + 3 * w, t);
          asm volatile("fence.proxy.async.shared::cta;" ::: "memory");
          OSTORE(t);
          asm volatile("cp.async.bulk.commit_group;" ::: "memory");
          asm volatile("cp.async.bulk.wait_group.read 0;" ::: "memory");
          TP(3 + 3 * w, t);
          if (t + 2 < kTilesPerCta) {
            mbar_expect_tx(bq, 16384);
            QLOAD(t + 2);
          } else {
            mbar_arrive(bq);
          }
        }
        asm volatile("cp.async.bulk.wait_group 0;" ::: "memory");
        mbar_arrive(bars + B_DONE + 8 * w);
      }
    }
  } else {
    asm volatile("setmaxnreg.inc.sync.aligned.u32 240;");
    const int wg = warp >> 2;
    const int my_bar = 1 + wg, other_bar = 2 - wg;
    const uint32_t bq = bars + B_FULLQ + 8 * wg, bo = bars + B_RDYO + 8 * wg;
    uint32_t qaddr;
    {
      const int row = (warp & 3) * 16 + (lane & 15);
      qaddr = sb + SM_QO + wg * 16384 + row * 128 + ((((uint32_t)lane >> 4) ^ (row & 7)) << 4);
    }
    float S[64], O[64];
    uint32_t P[32], Q[32];
    float l0, l1;
    const uint32_t dK = (((sb + SM_K) & 0x3FFFF) >> 4) | (1u << 16);
    const uint32_t dV = (((sb + SM_V) & 0x3FFFF) >> 4) | (1024u << 16);
    const uint32_t lane0 = (lane == 0);
    const uint32_t flag = bars + B_FLAG + 16 * wg;
    const uint32_t eK = mapa(bars + B_EMPTYK, 0), eV = mapa(bars + B_EMPTYV, 1);

    if (wg == 1) bar_arrive(other_bar);

    TR(0, 0);
    mbar_wait(bq, 0);
    load_q<true>(Q, qaddr);
    __syncwarp();
    if (lane == 0) mbar_arrive(bo);
    TRW(0, 3);
    mbar_wait(bars + B_FULLK, 0);
    TR(0, 1);
    bar_sync(my_bar);
    TR(0, 2);
    wg_fence();
    issue_qk(S, Q, dK);
    bar_arrive(other_bar);
    TR(0, 3);
    wg_wait<0>();
    fence_regs(S);
    TR(0, 4);
    if (lane == 0) mbar_arrive_cl(eK);
    exp_part<0, 64, true>(S, l0, l1);
#pragma unroll
    for (int i = 0; i < 32; i++) P[i] = pack_bf16(S[2 * i], S[2 * i + 1]);

#define STEP(J, KS, VS, RELK, RELV)                                            \
  do {                                                                         \
    TR(4 * t + (J ? J : 4), 1);                                                \
    bar_sync(my_bar);                                                          \
    TR(4 * t + (J ? J : 4), 2);                                                \
    if (J != 1) fence_regs(O);                                                 \
    wg_fence();                                                                \
    issue_qk(S, Q, dK + (KS) * 2048);                                          \
    issue_pv<J == 1>(O, P, dV + (VS) * 2048);                                  \
    bar_arrive(other_bar);                                                     \
    TR(4 * t + (J ? J : 4), 3);                                                \
    wg_wait<1>();                                                              \
    fence_regs(S);                                                             \
    TR(4 * t + (J ? J : 4), 4);                                                \
    const float lf0 = l0, lf1 = l1;                                            \
    if (J == 3) {                                                              \
      fence_regs(Q);                                                           \
      load_q<true>(Q, qaddr);                                                        \
    }                                                                          \
    exp_part<0, N1, J == 0>(S, l0, l1);                                        \
    mbar_arrive_anchor(eK + 8 * (KS), RELK, l0, l1);                           \
    TR(4 * t + (J ? J : 4), 5);                                                \
    wg_wait<0>();                                                              \
    fence_regs(O);                                                             \
    fence_regs(P);                                                             \
    TR(4 * t + (J ? J : 4), 6);                                                \
    exp_part<N1, 64, false>(S, l0, l1);                                        \
    _Pragma("unroll") for (int j = 0; j < 32; j++) P[j] = pack_bf16(S[2 * j], S[2 * j + 1]); \
    mbar_arrive_anchor(eV + 8 * (VS), RELV, l0, l1);                           \
    if (J == 0) {                                                              \
      epilogue<true>(O, lf0, lf1, qaddr, flag + t);                            \
      __syncwarp();                                                            \
      if (lane == 0) mbar_arrive(bo);                                          \
    }                                                                          \
    TR(4 * t + (J ? J : 4), 7);                                                \
  } while (0)

    constexpr int N1 = 40;
    uint32_t X = 0, s1 = 1, s2 = 2, mk = 1, mv = 0;
#define WAITK(sl) do { mbar_wait(bars + B_FULLK + 8 * (sl), (mk >> (sl)) & 1); mk ^= 1u << (sl); } while (0)
#define WAITV(sl) do { mbar_wait(bars + B_FULLV + 8 * (sl), (mv >> (sl)) & 1); mv ^= 1u << (sl); } while (0)
    bool first = true;
#pragma unroll 1
    for (int t = 0;; t++) {
      const bool last = ((v0 + t) & 3) == 3;
      const uint32_t rel = last ? lane0 : 0;
      TR(4 * t + 1, 0);
      if (first) {
        WAITK(s1);
        TRW(4 * t + 1, 3);
        WAITV(X);
      }
      STEP(1, s1, X, rel, lane0);
      TR(4 * t + 2, 0);
      if (first) {
        WAITK(s2);
        TRW(4 * t + 2, 3);
        WAITV(s1);
      }
      STEP(2, s2, s1, rel, rel);
      TR(4 * t + 3, 0);
      WAITK(X);
      TRW(4 * t + 3, 3);
      if (first) WAITV(s2);
      TRW(4 * t + 3, 4);
      mbar_wait(bq, (t + 1) & 1);
      STEP(3, X, s2, rel, rel);
      TR(4 * t + 4, 0);
      WAITV(X);
      TRW(4 * t + 4, 3);
      if (t == kTilesPerCta - 1) break;
      const uint32_t Xn = last ? s1 : X;
      if (last) WAITK(Xn);
      STEP(0, Xn, X, lane0, rel);
      const uint32_t n2 = last ? X : s1;
      s1 = s2;
      s2 = n2;
      X = Xn;
      first = last;
    }
    TR(64, 1);
    bar_sync(my_bar);
    TR(64, 2);
    fence_regs(O);
    wg_fence();
    issue_pv<false>(O, P, dV + X * 2048);
    if (wg == 0) bar_arrive(other_bar);
    wg_wait<0>();
    fence_regs(O);
    TR(64, 6);
    epilogue<true>(O, l0, l1, qaddr, flag + kTilesPerCta - 1);
    __syncwarp();
    if (lane == 0) mbar_arrive(bo);
    TR(64, 7);
    TRG(2);
    asm volatile("barrier.cluster.arrive.release;" ::: "memory");
    cluster_wait();

    uint32_t f0, f1, f2, f3;
    asm volatile("ld.shared.v4.u32 {%0,%1,%2,%3}, [%4];" : "=r"(f0), "=r"(f1), "=r"(f2), "=r"(f3) : "r"(flag) : "memory");
    if (f0 | f1 | f2 | f3) {
      const uint32_t bfb = bars + B_FB + 8 * wg;
      const uint32_t buf = sb + SM_QO + wg * 16384;
      const bool elect = (threadIdx.x & 127) == 0;
      uint32_t ph = 0;
      mbar_wait(bars + B_DONE + 8 * wg, 0);
#pragma unroll 1
      for (int t = 0; t < kTilesPerCta; t++) {
        uint32_t f;
        asm volatile("ld.shared.u8 %0, [%1];" : "=r"(f) : "r"(flag + t) : "memory");
        if (!f) continue;
        const int g = head_of((v0 + t) >> 2);
        float m0 = -INFINITY, m1 = -INFINITY;
        l0 = l1 = 0.f;
#pragma unroll
        for (int i = 0; i < 64; i++) O[i] = 0.f;
#pragma unroll 1
        for (int j = 0; j < 4; j++) {
          if (elect) {
            mbar_expect_tx(bfb, j ? 65536 : 81920);
            if (!j) tma_load3(buf, &tmQ, bfb, qrow(t, wg));
            tma_load3(sb + SM_K + wg * 32768, &tmK, bfb, g * kSeq + j * 128);
            tma_load3(sb + SM_V + wg * 32768, &tmV, bfb, g * kSeq + j * 128);
          }
          __syncwarp();
          mbar_wait(bfb, ph);
          ph ^= 1;
          if (!j) load_q<false>(Q, qaddr);
          fence_regs(Q);
          wg_fence();
          issue_qk(S, Q, dK + wg * 2048);
          wg_wait<0>();
          fence_regs(S);
          float a0, a1;
          softmax_block(S, m0, m1, l0, l1, a0, a1);
#pragma unroll
          for (int i = 0; i < 64; i++) O[i] *= (i & 2) ? a1 : a0;
#pragma unroll
          for (int i = 0; i < 32; i++) P[i] = pack_bf16(S[2 * i], S[2 * i + 1]);
          fence_regs(O);
          fence_regs(P);
          wg_fence();
          issue_pv<false>(O, P, dV + wg * 2048);
          wg_wait<0>();
          fence_regs(O);
          asm volatile("bar.sync %0, 128;" ::"r"(3 + wg) : "memory");
        }
        epilogue<false>(O, l0, l1, qaddr, 0);
        asm volatile("fence.proxy.async.shared::cta;" ::: "memory");
        asm volatile("bar.sync %0, 128;" ::"r"(3 + wg) : "memory");
        if (elect) {
          tma_store3(buf, &tmO, qrow(t, wg));
          asm volatile("cp.async.bulk.commit_group;" ::: "memory");
          asm volatile("cp.async.bulk.wait_group 0;" ::: "memory");
        }
      }
    }
  }
}

typedef CUresult (*EncodeTiledFn)(CUtensorMap*, CUtensorMapDataType, cuuint32_t, void*, const cuuint64_t*, const cuuint64_t*,
                                  const cuuint32_t*, const cuuint32_t*, CUtensorMapInterleave, CUtensorMapSwizzle,
                                  CUtensorMapL2promotion, CUtensorMapFloatOOBfill);

void make_map(EncodeTiledFn fn, CUtensorMap* tm, const void* ptr, uint64_t rows, uint32_t box_rows) {
  cuuint64_t dims[3] = {64, rows, 2};
  cuuint64_t strides[2] = {256, 128};
  cuuint32_t box[3] = {64, box_rows, 2};
  cuuint32_t estr[3] = {1, 1, 1};
  fn(tm, CU_TENSOR_MAP_DATA_TYPE_BFLOAT16, 3, const_cast<void*>(ptr), dims, strides, box, estr, CU_TENSOR_MAP_INTERLEAVE_NONE,
     CU_TENSOR_MAP_SWIZZLE_128B, CU_TENSOR_MAP_L2_PROMOTION_L2_256B, CU_TENSOR_MAP_FLOAT_OOB_FILL_NONE);
}

}

extern "C" void kernel_launch(void* const* d_in, const int* in_sizes, int n_in, void* d_out, int out_size) {
  (void)in_sizes;
  (void)n_in;
  (void)out_size;
  static EncodeTiledFn fn = nullptr;
  if (!fn) {
    void* p = nullptr;
    cudaDriverEntryPointQueryResult qr;
    cudaGetDriverEntryPoint("cuTensorMapEncodeTiled", &p, cudaEnableDefault, &qr);
    fn = (EncodeTiledFn)p;
    cudaFuncSetAttribute(gqa_attn_kernel, cudaFuncAttributeMaxDynamicSharedMemorySize, SMEM_BYTES);
  }
  CUtensorMap tmQ, tmK, tmV, tmO;
  make_map(fn, &tmQ, d_in[0], (uint64_t)kBatch * kHq * kSeq, 64);
  make_map(fn, &tmK, d_in[1], (uint64_t)kBatch * kHkv * kSeq, 128);
  make_map(fn, &tmV, d_in[2], (uint64_t)kBatch * kHkv * kSeq, 128);
  make_map(fn, &tmO, d_out, (uint64_t)kBatch * kHq * kSeq, 64);
  gqa_attn_kernel<<<kNumCtas, 384, SMEM_BYTES>>>(tmQ, tmK, tmV, tmO, (const uint8_t*)d_in[0], (const uint8_t*)d_in[1], (const uint8_t*)d_in[2]);
}
```

```cpp
#include <cuda_runtime.h>
#include <cuda_bf16.h>
#include <cuda.h>
#include <stdint.h>

namespace {

constexpr int kSeq = 512;
constexpr int kBatch = 16;
constexpr int kHq = 32;
constexpr int kHkv = 16;
constexpr int kNumCtas = 132;
constexpr int kTilesPerCta = 16;

constexpr uint32_t SM_K = 0;
constexpr uint32_t SM_V = 98304;
constexpr uint32_t SM_QO = 196608;
constexpr uint32_t SM_BAR = 229376;
constexpr uint32_t SM_L = SM_BAR + 256;
constexpr uint32_t SMEM_BYTES = SM_L + 1024 + 1024;

constexpr uint32_t B_FULLK = 0;
constexpr uint32_t B_EMPTYK = 32;
constexpr uint32_t B_FULLV = 64;
constexpr uint32_t B_EMPTYV = 96;
constexpr uint32_t B_FULLQ = 128;
constexpr uint32_t B_RDYO = 144;
constexpr uint32_t B_DONE = 160;
constexpr uint32_t B_FB = 176;
constexpr uint32_t B_FULLQ0 = 192;
constexpr uint32_t B_SCRATCH = 208;
constexpr uint32_t B_FLAG = 224;


constexpr int kSpinLimit = 4000000;
constexpr uint32_t T1 = 2000, T2 = 3000, T3 = 4500, T4 = 6000, T5 = 7500, TQ2 = 12000;
constexpr int kPrefetchDist = 2;
constexpr int N1 = 40;
constexpr int EA = 4;


__device__ __forceinline__ void mbar_init(uint32_t bar, uint32_t cnt) {
  asm volatile("mbarrier.init.shared::cta.b64 [%0], %1;" ::"r"(bar), "r"(cnt) : "memory");
}
__device__ __forceinline__ void mbar_arrive(uint32_t bar) {
  asm volatile("mbarrier.arrive.shared::cta.b64 _, [%0];" ::"r"(bar) : "memory");
}
__device__ __forceinline__ void mbar_expect_tx(uint32_t bar, uint32_t bytes) {
  asm volatile("mbarrier.arrive.expect_tx.shared::cta.b64 _, [%0], %1;" ::"r"(bar), "r"(bytes) : "memory");
}
__device__ __forceinline__ void mbar_wait(uint32_t bar, uint32_t parity) {
  asm volatile(
      "{\n"
      ".reg .pred p;\n"
      ".reg .u32 c;\n"
      "mbarrier.test_wait.parity.shared::cta.b64 p, [%0], %1;\n"
      "@p bra DONE;\n"
      "mov.u32 c, 0;\n"
      "LOOP:\n"
      "mbarrier.try_wait.parity.shared::cta.b64 p, [%0], %1;\n"
      "@p bra DONE;\n"
      "add.u32 c, c, 1;\n"
      "setp.lt.u32 p, c, %2;\n"
      "@p bra LOOP;\n"
      "trap;\n"
      "DONE:\n"
      "}\n" ::"r"(bar), "r"(parity), "n"(kSpinLimit) : "memory");
}
__device__ __forceinline__ uint32_t mbar_test(uint32_t bar, uint32_t parity) {
  uint32_t ok;
  asm volatile("{.reg .pred p; mbarrier.test_wait.parity.shared::cta.b64 p, [%1], %2; @!p st.shared.u32 [%1+80], %2; selp.u32 %0, 1, 0, p;}" : "=r"(ok) : "r"(bar), "r"(parity) : "memory");
  return ok;
}
__device__ __forceinline__ void tma_load3(uint32_t dst, const CUtensorMap* tm, uint32_t bar, int row) {
  asm volatile(
      "cp.async.bulk.tensor.3d.shared::cluster.global.mbarrier::complete_tx::bytes [%0], [%1, {%3, %4, %3}], [%2];" ::"r"(dst),
      "l"(tm), "r"(bar), "r"(0), "r"(row)
      : "memory");
}
__device__ __forceinline__ void tma_store3(uint32_t src, const CUtensorMap* tm, int row) {
  asm volatile("cp.async.bulk.tensor.3d.global.shared::cta.bulk_group [%1, {%2, %3, %2}], [%0];" ::"r"(src), "l"(tm), "r"(0),
               "r"(row)
               : "memory");
}
__device__ __forceinline__ void tma_load3_hint(uint32_t dst, const CUtensorMap* tm, uint32_t bar, int row, uint64_t pol) {
  asm volatile(
      "cp.async.bulk.tensor.3d.shared::cluster.global.mbarrier::complete_tx::bytes.L2::cache_hint [%0], [%1, {%3, %4, %3}], [%2], %5;" ::"r"(dst),
      "l"(tm), "r"(bar), "r"(0), "r"(row), "l"(pol)
      : "memory");
}
__device__ __forceinline__ void tma_store3_hint(uint32_t src, const CUtensorMap* tm, int row, uint64_t pol) {
  asm volatile("cp.async.bulk.tensor.3d.global.shared::cta.bulk_group.L2::cache_hint [%1, {%2, %3, %2}], [%0], %4;" ::"r"(src), "l"(tm), "r"(0),
               "r"(row), "l"(pol)
               : "memory");
}
__device__ __forceinline__ void tma_load3_mc(uint32_t dst, const CUtensorMap* tm, uint32_t bar, int row) {
  asm volatile(
      "cp.async.bulk.tensor.3d.shared::cluster.global.mbarrier::complete_tx::bytes.multicast::cluster [%0], [%1, {%3, %4, %3}], [%2], %5;" ::"r"(dst),
      "l"(tm), "r"(bar), "r"(0), "r"(row), "h"((uint16_t)3)
      : "memory");
}
__device__ __forceinline__ void tma_load3_mc_hint(uint32_t dst, const CUtensorMap* tm, uint32_t bar, int row, uint64_t pol) {
  asm volatile(
      "cp.async.bulk.tensor.3d.shared::cluster.global.mbarrier::complete_tx::bytes.multicast::cluster.L2::cache_hint [%0], [%1, {%3, %4, %3}], [%2], %5, %6;" ::"r"(dst),
      "l"(tm), "r"(bar), "r"(0), "r"(row), "h"((uint16_t)3), "l"(pol)
      : "memory");
}
__device__ __forceinline__ uint32_t mapa(uint32_t addr, uint32_t rank) {
  uint32_t r;
  asm("mapa.shared::cluster.u32 %0, %1, %2;" : "=r"(r) : "r"(addr), "r"(rank));
  return r;
}
__device__ __forceinline__ void mbar_arrive_cl(uint32_t bar) {
  asm volatile("mbarrier.arrive.shared::cluster.b64 _, [%0];" ::"r"(bar) : "memory");
}
__device__ __forceinline__ void mbar_expect_tx_cl(uint32_t bar, uint32_t bytes) {
  asm volatile("mbarrier.arrive.expect_tx.shared::cluster.b64 _, [%0], %1;" ::"r"(bar), "r"(bytes) : "memory");
}
__device__ __forceinline__ void cluster_arrive() { asm volatile("barrier.cluster.arrive.relaxed;" ::: "memory"); }
__device__ __forceinline__ void cluster_wait() { asm volatile("barrier.cluster.wait;" ::: "memory"); }
__device__ __forceinline__ uint64_t policy_evict_first() {
  uint64_t p;
  asm volatile("createpolicy.fractional.L2::evict_first.b64 %0, 1.0;" : "=l"(p));
  return p;
}
__device__ __forceinline__ void l2_prefetch(const void* p, uint32_t bytes) {
  asm volatile("cp.async.bulk.prefetch.L2.global [%0], %1;" ::"l"(p), "r"(bytes) : "memory");
}

#define R8(a, i) "+f"(a[i + 0]), "+f"(a[i + 1]), "+f"(a[i + 2]), "+f"(a[i + 3]), "+f"(a[i + 4]), "+f"(a[i + 5]), "+f"(a[i + 6]), "+f"(a[i + 7])
#define ACC64(a) R8(a, 0), R8(a, 8), R8(a, 16), R8(a, 24), R8(a, 32), R8(a, 40), R8(a, 48), R8(a, 56)
#define W8(a, i) "=f"(a[i + 0]), "=f"(a[i + 1]), "=f"(a[i + 2]), "=f"(a[i + 3]), "=f"(a[i + 4]), "=f"(a[i + 5]), "=f"(a[i + 6]), "=f"(a[i + 7])
#define OUT64(a) W8(a, 0), W8(a, 8), W8(a, 16), W8(a, 24), W8(a, 32), W8(a, 40), W8(a, 48), W8(a, 56)
#define D64                                                                                                      \
  "{%0,%1,%2,%3,%4,%5,%6,%7,%8,%9,%10,%11,%12,%13,%14,%15,%16,%17,%18,%19,%20,%21,%22,%23,%24,%25,%26,%27,%28,"  \
  "%29,%30,%31,%32,%33,%34,%35,%36,%37,%38,%39,%40,%41,%42,%43,%44,%45,%46,%47,%48,%49,%50,%51,%52,%53,%54,%55," \
  "%56,%57,%58,%59,%60,%61,%62,%63}"

template <int TB>
__device__ __forceinline__ void wgmma_rs(float (&d)[64], const uint32_t* a, uint64_t db, int scale_d) {
  asm volatile(
      "{\n.reg .pred p;\nsetp.ne.b32 p, %69, 0;\n"
      "wgmma.mma_async.sync.aligned.m64n128k16.f32.bf16.bf16 " D64 ", {%64,%65,%66,%67}, %68, p, 1, 1, %70;\n}\n"
      : ACC64(d)
      : "r"(a[0]), "r"(a[1]), "r"(a[2]), "r"(a[3]), "l"(db), "r"(scale_d), "n"(TB));
}
template <int TB>
__device__ __forceinline__ void wgmma_rs_zero(float (&d)[64], const uint32_t* a, uint64_t db) {
  asm volatile(
      "{\n.reg .pred p;\nsetp.ne.b32 p, 0, 0;\n"
      "wgmma.mma_async.sync.aligned.m64n128k16.f32.bf16.bf16 " D64 ", {%64,%65,%66,%67}, %68, p, 1, 1, %69;\n}\n"
      : OUT64(d)
      : "r"(a[0]), "r"(a[1]), "r"(a[2]), "r"(a[3]), "l"(db), "n"(TB));
}
__device__ __forceinline__ void wg_fence() { asm volatile("wgmma.fence.sync.aligned;" ::: "memory"); }
__device__ __forceinline__ void wg_commit() { asm volatile("wgmma.commit_group.sync.aligned;" ::: "memory"); }
template <int N>
__device__ __forceinline__ void wg_wait() {
  asm volatile("wgmma.wait_group.sync.aligned %0;" ::"n"(N) : "memory");
}
__device__ __forceinline__ void fence_regs(float (&d)[64]) {
#pragma unroll
  for (int i = 0; i < 64; i++) asm volatile("" : "+f"(d[i])::"memory");
}
__device__ __forceinline__ void fence_regs(uint32_t (&d)[32]) {
#pragma unroll
  for (int i = 0; i < 32; i++) asm volatile("" : "+r"(d[i])::"memory");
}
__device__ __forceinline__ float ex2(float x) {
  float y;
  asm("ex2.approx.ftz.f32 %0, %1;" : "=f"(y) : "f"(x));
  return y;
}
__device__ __forceinline__ uint32_t pack_bf16(float lo, float hi) {
  uint32_t r;
  asm("cvt.rn.bf16x2.f32 %0, %1, %2;" : "=r"(r) : "f"(hi), "f"(lo));
  return r;
}
__device__ __forceinline__ void ldsm4(uint32_t* r, uint32_t addr) {
  asm volatile("ldmatrix.sync.aligned.m8n8.x4.shared.b16 {%0,%1,%2,%3}, [%4];"
               : "=r"(r[0]), "=r"(r[1]), "=r"(r[2]), "=r"(r[3])
               : "r"(addr)
               : "memory");
}
__device__ __forceinline__ void stsm4(uint32_t addr, uint32_t r0, uint32_t r1, uint32_t r2, uint32_t r3) {
  asm volatile("stmatrix.sync.aligned.m8n8.x4.shared.b16 [%0], {%1,%2,%3,%4};" ::"r"(addr), "r"(r0), "r"(r1), "r"(r2), "r"(r3)
               : "memory");
}
__device__ __forceinline__ void bar_sync(int id) { asm volatile("bar.sync %0, 256;" ::"r"(id) : "memory"); }
__device__ __forceinline__ void bar_arrive(int id) { asm volatile("bar.arrive %0, 256;" ::"r"(id) : "memory"); }

__device__ __forceinline__ uint64_t slot_desc(uint64_t base, int slot) {
  uint64_t d;
  asm volatile("mad.wide.s32 %0, %1, 2048, %2;" : "=l"(d) : "r"(slot), "l"(base));
  return d;
}
__device__ __forceinline__ void issue_qk(float (&S)[64], const uint32_t (&Q)[32], uint64_t d0) {
  wgmma_rs_zero<0>(S, &Q[0], d0);
#pragma unroll
  for (int kk = 1; kk < 8; kk++) wgmma_rs<0>(S, &Q[4 * kk], d0 + (((kk / 4) * 16384 + (kk % 4) * 32) >> 4), 1);
  wg_commit();
}
template <bool ZERO>
__device__ __forceinline__ void issue_pv(float (&O)[64], const uint32_t (&P)[32], uint64_t d0) {
  if (ZERO)
    wgmma_rs_zero<1>(O, &P[0], d0);
  else
    wgmma_rs<1>(O, &P[0], d0, 1);
#pragma unroll
  for (int kk = 1; kk < 8; kk++) wgmma_rs<1>(O, &P[4 * kk], d0 + ((kk * 2048) >> 4), 1);
  wg_commit();
}

template <int LO, int HI, bool INIT>
__device__ __forceinline__ void exp_part(float (&S)[64], float& l0, float& l1) {
#pragma unroll
  for (int j = LO; j < HI; j++) {
    S[j] = ex2(S[j]);
    if (INIT && j == 0)
      l0 = S[j];
    else if (INIT && j == 2)
      l1 = S[j];
    else if (j & 2)
      l1 += S[j];
    else
      l0 += S[j];
  }
}
__device__ __forceinline__ void anchor(uint32_t addr, float l0, float l1) {
  asm volatile(
      "{\n.reg .pred p;\n.reg .f32 n;\n"
      "neg.f32 n, %2;\n"
      "setp.lt.f32 p, %1, n;\n"
      "@p mbarrier.arrive.shared::cta.b64 _, [%0];\n}\n" ::"r"(addr),
      "f"(l0), "f"(l1)
      : "memory");
}
__device__ __forceinline__ void mbar_arrive_cl_pred(uint32_t bar, uint32_t pred) {
  asm volatile(
      "{\n.reg .pred q;\n"
      "setp.ne.u32 q, %1, 0;\n"
      "@q mbarrier.arrive.shared::cluster.b64 _, [%0];\n}\n" ::"r"(bar),
      "r"(pred)
      : "memory");
}

template <bool SCALE>
__device__ __forceinline__ void load_q(uint32_t (&Q)[32], uint32_t qaddr) {
#pragma unroll
  for (int kk = 0; kk < 8; kk++) ldsm4(&Q[4 * kk], (qaddr ^ ((kk % 4) * 32)) + (kk / 4) * 8192);
  if (SCALE) {
#pragma unroll
    for (int j = 0; j < 32; j++)
      asm("{.reg .b32 t; mul.rn.bf16x2 t, %0, %1; fma.rn.bf16x2 %0, t, %2, t;}" : "+r"(Q[j]) : "r"(0x3E003E00u), "r"(0x3CA53CA5u));
  }
}

template <bool CHECK>
__device__ __forceinline__ void row_inv(float l0, float l1, float& i0, float& i1, uint32_t flag) {
  l0 += __shfl_xor_sync(0xffffffffu, l0, 1);
  l1 += __shfl_xor_sync(0xffffffffu, l1, 1);
  l0 += __shfl_xor_sync(0xffffffffu, l0, 2);
  l1 += __shfl_xor_sync(0xffffffffu, l1, 2);
  if (CHECK) {
    constexpr uint32_t lo = (127u - 24u) << 23;
    const uint32_t bad = ((__float_as_uint(l0) - lo) | (__float_as_uint(l1) - lo)) & 0xE0000000u;
    asm volatile("{.reg .pred p; setp.ne.u32 p, %1, 0; @p st.shared.u8 [%0], %0;}" ::"r"(flag), "r"(bad) : "memory");
  }
  asm("rcp.approx.ftz.f32 %0, %1;" : "=f"(i0) : "f"(l0));
  asm("rcp.approx.ftz.f32 %0, %1;" : "=f"(i1) : "f"(l1));
}
template <int LO, int HI>
__device__ __forceinline__ void store_o(float (&O)[64], float i0, float i1, uint32_t qaddr) {
#pragma unroll
  for (int kk = LO; kk < HI; kk++) {
    const uint32_t r0 = pack_bf16(O[8 * kk + 0] * i0, O[8 * kk + 1] * i0);
    const uint32_t r1 = pack_bf16(O[8 * kk + 2] * i1, O[8 * kk + 3] * i1);
    const uint32_t r2 = pack_bf16(O[8 * kk + 4] * i0, O[8 * kk + 5] * i0);
    const uint32_t r3 = pack_bf16(O[8 * kk + 6] * i1, O[8 * kk + 7] * i1);
    stsm4((qaddr ^ ((kk % 4) * 32)) + (kk / 4) * 8192, r0, r1, r2, r3);
  }
}

__device__ __forceinline__ void softmax_block(float (&S)[64], float& m0, float& m1, float& l0, float& l1, float& a0, float& a1) {
  constexpr float c = 0.08838834764831845f * 1.4426950408889634f;
  float y0 = fmaxf(S[0], S[1]), y1 = fmaxf(S[2], S[3]);
#pragma unroll
  for (int j = 1; j < 16; j++) {
    y0 = fmaxf(y0, fmaxf(S[4 * j], S[4 * j + 1]));
    y1 = fmaxf(y1, fmaxf(S[4 * j + 2], S[4 * j + 3]));
  }
  y0 = fmaxf(y0, __shfl_xor_sync(0xffffffffu, y0, 1));
  y1 = fmaxf(y1, __shfl_xor_sync(0xffffffffu, y1, 1));
  y0 = fmaxf(y0, __shfl_xor_sync(0xffffffffu, y0, 2));
  y1 = fmaxf(y1, __shfl_xor_sync(0xffffffffu, y1, 2));
  const float n0 = fmaxf(m0, y0 * c), n1 = fmaxf(m1, y1 * c);
  const float e0 = n0 == -INFINITY ? 0.f : n0, e1 = n1 == -INFINITY ? 0.f : n1;
  a0 = ex2(m0 - e0);
  a1 = ex2(m1 - e1);
  m0 = n0;
  m1 = n1;
  l0 *= a0;
  l1 *= a1;
#pragma unroll
  for (int j = 0; j < 16; j++) {
    S[4 * j + 0] = ex2(fmaf(S[4 * j + 0], c, -e0));
    S[4 * j + 1] = ex2(fmaf(S[4 * j + 1], c, -e0));
    S[4 * j + 2] = ex2(fmaf(S[4 * j + 2], c, -e1));
    S[4 * j + 3] = ex2(fmaf(S[4 * j + 3], c, -e1));
    l0 += S[4 * j + 0] + S[4 * j + 1];
    l1 += S[4 * j + 2] + S[4 * j + 3];
  }
}

struct Map {
  int par, grp;
  bool vip;
  uint32_t lastm, blo, bhi;
  __device__ __forceinline__ Map(uint32_t bid) {
    par = bid & 1;
    const int cl = (int)(bid >> 1) - 30;
    vip = (unsigned)cl < 2u;
    const int cc = (int)(bid >> 1) - (cl >= 2 ? 2 : 0);
    const int ty = vip ? 8 + cl : cc & 7;
    grp = cc >> 3;
    constexpr uint32_t L[5] = {0x1445, 0x2222, 0x1111, 0x288a, 0x888};
    constexpr uint32_t BL[10] = {0x824a1e08, 0xac743410, 0x9e66260a, 0x90583c18, 0x8a52220c,
                                 0xb47c4414, 0xa66e2e0e, 0x9860401c, 0x20181008, 0x28201810};
    constexpr uint32_t BH[10] = {0xc6ba, 0xc9, 0xce, 0xd1c0, 0xd6be, 0xd9, 0xde, 0xe1c4, 0, 0};
    const int y = cc & 3;
    lastm = vip ? L[4] : y == 0 ? L[0] : y == 1 ? L[1] : y == 2 ? L[2] : L[3];
    blo = BL[0], bhi = BH[0];
#pragma unroll
    for (int i = 1; i < 10; i++)
      if (ty == i) blo = BL[i], bhi = BH[i];
  }
  __device__ __forceinline__ int unit(int t) const {
    const int seg = __popc(lastm & ((1u << t) - 1));
    return (int)(__byte_perm(blo, bhi, seg) & 255) + 2 * t - 8;
  }
  __device__ __forceinline__ int head_of(int x) const { return vip ? x >> 3 : (x & ~7) + 8 + grp; }
  __device__ __forceinline__ int head_at(int t) const { return head_of(unit(t)); }
  __device__ __forceinline__ int qrow(int t, int w) const {
    const int x = unit(t) + ((t == 15 && !vip) ? 0 : w);
    return ((head_of(x) * 2 + par) * 8 + (x & 7)) * 64;
  }
};

__global__ void __cluster_dims__(2, 1, 1) __launch_bounds__(384, 1)
gqa_attn_kernel(const __grid_constant__ CUtensorMap tmQ, const __grid_constant__ CUtensorMap tmK,
                const __grid_constant__ CUtensorMap tmV, const __grid_constant__ CUtensorMap tmO,
                const uint8_t* __restrict__ gq, const uint8_t* __restrict__ gk, const uint8_t* __restrict__ gv,
                uint8_t* __restrict__ go,
                const uint64_t desck, const uint64_t descv) {
  extern __shared__ __align__(1024) uint8_t smem_raw[];
  const uint32_t sb = ((uint32_t)__cvta_generic_to_shared(smem_raw) + 1023u) & ~1023u;
  const uint32_t bars = sb + SM_BAR;
  const int warp = __shfl_sync(0xffffffffu, (int)(threadIdx.x >> 5), 0);
  const int lane = threadIdx.x & 31;
  const Map mp(blockIdx.x);
  const int par = mp.par;
  const bool vip = mp.vip;
  const uint32_t lastm0 = mp.lastm;
  auto head_at = [&](int t) { return mp.head_at(t); };
  auto qrow = [&](int t, int w) { return mp.qrow(t, w); };
  auto kvrow = [&](int g, int blk) { return g * kSeq + blk * 128; };
  uint32_t t0;
  asm volatile("mov.u32 %0, %%clock;" : "=r"(t0)::"memory");
  if (vip) t0 -= 0x100000;
  auto wait_until = [&](uint32_t dt) {
    uint32_t c;
    do {
      asm volatile("mov.u32 %0, %%clock;" : "=r"(c)::"memory");
    } while (c - t0 < dt);
  };
  if (lane == 0) {
    if (warp == 8) asm volatile("prefetch.tensormap [%0];" ::"l"(par ? &tmV : &tmK) : "memory");
    if (warp == 10) {
      l2_prefetch(gq + (size_t)qrow(0, 0) * 256, 16384);
      asm volatile("prefetch.tensormap [%0];" ::"l"(&tmQ) : "memory");
    }
    if (warp == 11) asm volatile("prefetch.tensormap [%0];" ::"l"(&tmO) : "memory");
    if (warp == 9 && !vip) {
      const uint32_t i = blockIdx.x - (blockIdx.x >= 64 ? 4 : 0), c = i >> 6;
      const uint32_t code = (0x1980u >> (4 * ((i & 63) >> 4))) & 15;
      const uint8_t* p = code >= 8 ? gq + (2 * c + code - 8) * 131072 : gk + c * 131072 + code * 32768;
      l2_prefetch(p + (i & 15) * 2048, 2048);
    }
    if (warp < 7) {
      const uint32_t c0 = (warp == 1 || warp == 3) ? 16 : 1, c1 = warp == 4 ? 4 : c0;
      mbar_init(bars + 32 * warp, c0);
      mbar_init(bars + 32 * warp + 8, c0);
      mbar_init(bars + 32 * warp + 16, c1);
      mbar_init(bars + 32 * warp + 24, c1);
      asm volatile("fence.mbarrier_init.release.cluster;" ::: "memory");
      asm volatile("fence.proxy.async.shared::cta;" ::: "memory");
    }
    if (warp == 7) {
      asm volatile("st.shared.v4.u32 [%0], {%1,%1,%1,%1};" ::"r"(bars + B_FLAG), "r"(0) : "memory");
      asm volatile("st.shared.v4.u32 [%0], {%1,%1,%1,%1};" ::"r"(bars + B_FLAG + 16), "r"(0) : "memory");
    }
  }
  __syncwarp();
  cluster_arrive();
  cluster_wait();

  if (warp >= 8) {
    asm volatile("setmaxnreg.dec.sync.aligned.u32 24;");
    if (lane == 0) {
      if (warp == 8) {
        const CUtensorMap* tm = par ? &tmV : &tmK;
        const uint32_t sbase = sb + (par ? SM_V : SM_K);
        const uint32_t bfull = bars + (par ? B_FULLV : B_FULLK);
        const uint32_t bfull_peer = mapa(bfull, par ^ 1);
        const uint32_t bempty = bfull + 32;
        const uint8_t* gp = par ? gv : gk;
        const uint64_t pol = policy_evict_first();
        uint32_t X = 0, s1 = 1, s2 = 2, pe = 7;
        int t = 0, f = 0, n_ld = 0, g = head_at(0);
#pragma unroll 1
        while (t < kTilesPerCta) {
          const uint32_t rest = lastm0 >> t;
          const int n = rest ? __ffs(rest) : kTilesPerCta - t;
          const int gn = head_at(rest ? t + n : t);
#pragma unroll 1
          for (int j = 0; j < n + 3; j++) {
            const int blk = j < 3 ? j : (j & 1) * 3;
            int slot = j == 1 ? s1 : j == 2 ? s2 : X;
            if (par && !vip && t + j == kTilesPerCta + 2) slot = ((n & 1) ? s2 : s1) - 3;
            const uint32_t role = min(j, 3);
            const int m = n_ld + par;
            if (m >= 1 && m <= 4) wait_until(m == 1 ? T2 : m == 2 ? T3 : m == 3 ? T4 : T5);
            mbar_wait(bempty + 8 * role, (pe >> role) & 1);
            pe ^= 1u << role;
            n_ld++;
            mbar_expect_tx(bfull + 8 * role, 32768);
            mbar_expect_tx_cl(bfull_peer + 8 * role, 32768);
            if (n == 4 && ((0x66 >> j) & 1))
              tma_load3_mc_hint(sbase + slot * 32768, tm, bfull + 8 * role, kvrow(g, blk), pol);
            else
              tma_load3_mc(sbase + slot * 32768, tm, bfull + 8 * role, kvrow(g, blk));
            f = max(f, min(j, 3));
            const int jj = kPrefetchDist - (n + 2 - j) - 1;
            int fm = jj >= 0 ? 4 + min(jj, 3) : min(j + kPrefetchDist, 3);
            if (m <= (vip ? 2 : 4)) fm = 0;
            if (!rest) fm = min(fm, 3);
#pragma unroll 1
            while (f < fm) {
              f++;
              l2_prefetch(gp + (size_t)kvrow(f > 3 ? gn : g, f & 3) * 256, 32768);
            }
          }
          const uint32_t a = (n & 1) ? s1 : s2, b = (n & 1) ? s2 : s1;
          s1 = b;
          s2 = X;
          X = a;
          t += n;
          f -= 4;
          g = gn;
        }
      } else if (warp >= 10) {
        const int w = warp - 10;
        const uint32_t buf = sb + SM_QO + w * 16384;
        const uint32_t bq = bars + B_FULLQ + 8 * w, bo = bars + B_RDYO + 8 * w;
        const uint64_t pol = policy_evict_first();
        if (w) wait_until(T1);
        mbar_expect_tx(bq + (B_FULLQ0 - B_FULLQ), 16384);
        tma_load3_hint(buf, &tmQ, bq + (B_FULLQ0 - B_FULLQ), qrow(0, w), pol);
        mbar_wait(bo, 0);
        wait_until(w ? T5 : T4);
        mbar_expect_tx(bq, 16384);
        tma_load3_hint(buf, &tmQ, bq, qrow(1, w), pol);
        wait_until(TQ2 + w * 1000);
        l2_prefetch(gq + (size_t)qrow(2, w) * 256, 16384);
#pragma unroll 1
        for (int t = 0; t < kTilesPerCta - 1; t++) {
          mbar_wait(bo, (t + 1) & 1);
          asm volatile("fence.proxy.async.shared::cta;" ::: "memory");
          tma_store3_hint(buf, &tmO, qrow(t, w), pol);
          asm volatile("cp.async.bulk.commit_group;" ::: "memory");
          asm volatile("cp.async.bulk.wait_group.read 0;" ::: "memory");
          if (t + 2 < kTilesPerCta) {
            mbar_expect_tx(bq, 16384);
            tma_load3_hint(buf, &tmQ, bq, qrow(t + 2, w), pol);
          } else {
            mbar_arrive(bq);
          }
          if (t + 3 < kTilesPerCta) {
            mbar_wait(bq, (t + 1) & 1);
            l2_prefetch(gq + (size_t)qrow(t + 3, w) * 256, 16384);
          }
        }
        asm volatile("cp.async.bulk.wait_group 0;" ::: "memory");
        mbar_arrive(bars + B_DONE + 8 * w);
      }
    }
  } else {
    asm volatile("setmaxnreg.inc.sync.aligned.u32 240;");
    const int wg = warp >> 2;
    const int my_bar = 1 + (threadIdx.x >> 7), other_bar = 2 - (threadIdx.x >> 7);
    const uint32_t bq = bars + B_FULLQ + 8 * wg, bo = bars + B_RDYO + 8 * wg;
    uint32_t qaddr;
    {
      const int row = (warp & 3) * 16 + (lane & 15);
      qaddr = sb + SM_QO + wg * 16384 + row * 128 + ((((uint32_t)lane >> 4) ^ (row & 7)) << 4);
    }
    float S[64], O[64];
    uint32_t P[32], Q[32];
    float l0, l1, i0 = 0.f, i1 = 0.f;
    const uint64_t dK = desck + ((sb & 0x3FFFF) >> 4), dV = descv + ((sb & 0x3FFFF) >> 4);
    uint32_t lane0 = (lane == 0);
    const uint32_t flag = bars + B_FLAG + 16 * wg;
    const uint32_t eK = mapa(bars + B_EMPTYK, 0), eV = mapa(bars + B_EMPTYV, 1);
    uint32_t eK3 = eK + 24;

    if (wg == 1) bar_arrive(other_bar);

    mbar_wait(bq + (B_FULLQ0 - B_FULLQ), 0);
    load_q<true>(Q, qaddr);
    __syncwarp();
    if (lane == 0) mbar_arrive(bo);
    mbar_wait(bars + B_FULLK, 0);
    bar_sync(my_bar);
    wg_fence();
    issue_qk(S, Q, dK);
    bar_arrive(other_bar);
    wg_wait<0>();
    fence_regs(S);
    if (lane == 0) mbar_arrive_cl(eK + 24);
    exp_part<0, 64, true>(S, l0, l1);
#pragma unroll
    for (int i = 0; i < 32; i++) P[i] = pack_bf16(S[2 * i], S[2 * i + 1]);
#pragma unroll
    for (int i = 0; i < 64; i++) asm volatile("" : "=f"(O[i]));

    uint32_t qok = 1;
#define STEP(J, KS, VS, RK, RELK, RV, RELV, VWAIT)                                            \
  do {                                                                                        \
    VWAIT;                                                                                    \
    if (J == 0 && !__all_sync(0xffffffffu, qok)) {    \
      mbar_wait(bq, t & 1);                                                                   \
      load_q<true>(Q, qaddr);                                                                 \
    }                                                                                         \
    bar_sync(my_bar);                                                                         \
    if (J != 1) fence_regs(O);                                                                \
    wg_fence();                                                                               \
    issue_qk(S, Q, slot_desc(dK, KS));                                                        \
    if (J == 1) {                                                                             \
      if (t) {                                                                                \
        store_o<EA, 8>(O, i0, i1, qaddr);                                                     \
        __syncwarp();                                                                         \
        if (lane == 0) mbar_arrive(bo);                                                       \
      }                                                                                       \
      fence_regs(O);                                                                          \
      wg_fence();                                                                             \
    }                                                                                         \
    issue_pv<J == 1>(O, P, slot_desc(dV, VS));                                                \
    bar_arrive(other_bar);                                                                    \
    wg_wait<1>();                                                                             \
    fence_regs(S);                                                                            \
    mbar_arrive_cl_pred(J == 0 ? eK3 : eK + 8 * (RK), RELK);                                  \
    if (J == 3) {                                                                             \
      qok = mbar_test(bq, t & 1);                                                             \
      fence_regs(Q);                                                                          \
      load_q<true>(Q, qaddr);                                                                 \
    }                                                                                         \
    if (J == 0) row_inv<true>(l0, l1, i0, i1, flag + t);                                      \
    exp_part<0, N1, J == 0>(S, l0, l1);                                                       \
    anchor(bo, l0, l1);                                                                       \
    wg_wait<0>();                                                                             \
    fence_regs(O);                                                                            \
    fence_regs(P);                                                                            \
    mbar_arrive_cl_pred(eV + 8 * (RV), RELV);                                                 \
    exp_part<N1, 64, false>(S, l0, l1);                                                       \
    _Pragma("unroll") for (int j = 0; j < 32; j++) P[j] = pack_bf16(S[2 * j], S[2 * j + 1]);  \
    anchor(bo, l0, l1);                                                                       \
    if (J == 0) store_o<0, EA>(O, i0, i1, qaddr);                                             \
  } while (0)

    int X = 0, s1 = 1, s2 = 2;
    uint32_t sp = 0;
    uint32_t lastm = lastm0;
    const int th = vip ? kTilesPerCta - 1 : kTilesPerCta - 2;
    bool first = true;
#pragma unroll 1
    for (int t = 0;; t++) {
      const bool last = lastm & 1;
      lastm >>= 1;
      const uint32_t rel = last ? lane0 : 0;
      if (first) {
        if (t == kTilesPerCta - 1) {
          lane0 = 0;
          const int x = s1;
          if (wg) {
            mbar_wait(bars + B_FULLK + 24, 1);
            s1 = s2;
          }
          s2 = x;
        } else {
          mbar_wait(bars + B_FULLK + 8, sp);
          mbar_wait(bars + B_FULLV, sp);
        }
      }
      STEP(1, s1, X, 0, rel, 3, lane0, );
      if (first) {
        if (t == kTilesPerCta - 1) {
          X = wg ? X - 3 : s1;
          break;
        }
        mbar_wait(bars + B_FULLK + 16, sp);
        mbar_wait(bars + B_FULLV + 8, sp);
      }
      STEP(2, s2, s1, 1, rel, 0, rel, );
      mbar_wait(bars + B_FULLK + 24, t & 1);
      STEP(3, X, s2, 2, rel, 1, rel, if (first) mbar_wait(bars + B_FULLV + 16, sp));
      bool rot = last;
      first = last;
      if (t >= th) {
        if (t == kTilesPerCta - 1) break;
        first = true;
        if (wg) {
          rot = true;
          mbar_arrive_cl_pred(eK3, lane0);
          eK3 = eV + 24;
        } else {
          mbar_wait(bars + B_FULLV + 24, t & 1);
          mbar_arrive_cl_pred(eV + 24, lane0);
        }
      }
      const int Xn = rot ? s1 : X;
      if (last) {
        sp ^= 1;
        mbar_wait(bars + B_FULLK, sp);
      }
      STEP(0, Xn, X, 3, lane0, 2, rel, mbar_wait(bars + B_FULLV + 24, t & 1));
      const int n2 = rot ? X : s1;
      s1 = s2;
      s2 = n2;
      X = Xn;
    }
    const uint32_t laddr = sb + SM_L + (threadIdx.x & 127) * 8;
    if (vip || wg) mbar_wait(bars + B_FULLV + 24, 1);
    if (!wg) asm volatile("st.shared.v2.f32 [%0], {%1,%2};" ::"r"(laddr), "f"(l0), "f"(l1) : "memory");
    bar_sync(my_bar);
    fence_regs(O);
    wg_fence();
    issue_pv<false>(O, P, slot_desc(dV, X));
    if (wg == 0) bar_arrive(other_bar);
    {
      float x0, x1;
      asm volatile("ld.shared.v2.f32 {%0,%1}, [%2];" : "=f"(x0), "=f"(x1) : "r"(laddr) : "memory");
      l0 += (!vip && wg) ? x0 : 0.f;
      l1 += (!vip && wg) ? x1 : 0.f;
    }
    row_inv<true>(l0, l1, i0, i1, (vip || wg) ? flag + kTilesPerCta - 1 : bars + B_SCRATCH);
    const int row_last = mp.qrow(kTilesPerCta - 1, wg) + (warp & 3) * 16;
    const uint32_t paddr = sb + SM_K + s2 * 32768 + (threadIdx.x & 127) * 16;
    wg_wait<0>();
    fence_regs(O);
    if (!vip && !wg) {
#pragma unroll
      for (int i = 0; i < 16; i++)
        asm volatile("st.shared.v4.f32 [%0], {%1,%2,%3,%4};" ::"r"(paddr + i * 2048), "f"(O[4 * i]), "f"(O[4 * i + 1]), "f"(O[4 * i + 2]), "f"(O[4 * i + 3]) : "memory");
      bar_arrive(5);
    } else {
      if (!vip) {
        bar_sync(5);
#pragma unroll
        for (int i = 0; i < 16; i++)
          asm volatile("ld.shared.v4.f32 {%0,%1,%2,%3}, [%4];" : "=f"(S[4 * i]), "=f"(S[4 * i + 1]), "=f"(S[4 * i + 2]), "=f"(S[4 * i + 3]) : "r"(paddr + i * 2048) : "memory");
#pragma unroll
        for (int i = 0; i < 64; i++) O[i] += S[i];
      }
      mbar_wait(bq, 1);
      {
        const int r = lane >> 3;
        const uint32_t raddr = sb + SM_QO + wg * 16384 + (warp & 3) * 2048 + r * 128 + (((lane & 7) ^ r) << 4);
        uint8_t* gdst = go + (size_t)(row_last + r) * 256 + (lane & 7) * 16;
#pragma unroll
        for (int h = 0; h < 2; h++) {
          if (h) store_o<4, 8>(O, i0, i1, qaddr);
          else store_o<0, 4>(O, i0, i1, qaddr);
          __syncwarp();
#pragma unroll
          for (int i = 0; i < 4; i++) {
            uint32_t a, b, c, d;
            asm volatile("ld.shared.v4.u32 {%0,%1,%2,%3}, [%4];" : "=r"(a), "=r"(b), "=r"(c), "=r"(d) : "r"((raddr ^ ((i & 1) * 64)) + i * 512 + h * 8192) : "memory");
            asm volatile("st.global.v4.u32 [%0], {%1,%2,%3,%4};" ::"l"(gdst + i * 1024 + h * 128), "r"(a), "r"(b), "r"(c), "r"(d) : "memory");
          }
        }
      }
    }
    cluster_arrive();
    asm volatile("bar.sync %0, 128;" ::"r"(3 + wg) : "memory");
    cluster_wait();

    uint32_t f0, f1, f2, f3;
    asm volatile("ld.shared.v4.u32 {%0,%1,%2,%3}, [%4];" : "=r"(f0), "=r"(f1), "=r"(f2), "=r"(f3) : "r"(flag) : "memory");
    if (f0 | f1 | f2 | f3) {
      const uint32_t bfb = bars + B_FB + 8 * wg;
      const uint32_t buf = sb + SM_QO + wg * 16384;
      const bool elect = (threadIdx.x & 127) == 0;
      uint32_t ph = 0;
      mbar_wait(bars + B_DONE + 8 * wg, 0);
      __threadfence();
      asm volatile("fence.proxy.async;" ::: "memory");
      asm volatile("bar.sync %0, 128;" ::"r"(3 + wg) : "memory");
      if (elect) asm volatile("fence.proxy.async.shared::cta;" ::: "memory");
#pragma unroll 1
      for (int t = 0; t < kTilesPerCta; t++) {
        uint32_t f;
        asm volatile("ld.shared.u8 %0, [%1];" : "=r"(f) : "r"(flag + t) : "memory");
        if (!f) continue;
        const int g = mp.head_at(t);
        float m0 = -INFINITY, m1 = -INFINITY;
        l0 = l1 = 0.f;
#pragma unroll
        for (int i = 0; i < 64; i++) O[i] = 0.f;
#pragma unroll 1
        for (int j = 0; j < 4; j++) {
          if (elect) {
            mbar_expect_tx(bfb, j ? 65536 : 81920);
            if (!j) tma_load3(buf, &tmQ, bfb, mp.qrow(t, wg));
            tma_load3(sb + SM_K + wg * 32768, &tmK, bfb, g * kSeq + j * 128);
            tma_load3(sb + SM_V + wg * 32768, &tmV, bfb, g * kSeq + j * 128);
          }
          __syncwarp();
          mbar_wait(bfb, ph);
          ph ^= 1;
          if (!j) load_q<false>(Q, qaddr);
          fence_regs(Q);
          wg_fence();
          issue_qk(S, Q, slot_desc(dK, wg));
          wg_wait<0>();
          fence_regs(S);
          float a0, a1;
          softmax_block(S, m0, m1, l0, l1, a0, a1);
#pragma unroll
          for (int i = 0; i < 64; i++) O[i] *= (i & 2) ? a1 : a0;
#pragma unroll
          for (int i = 0; i < 32; i++) P[i] = pack_bf16(S[2 * i], S[2 * i + 1]);
          fence_regs(O);
          fence_regs(P);
          wg_fence();
          issue_pv<false>(O, P, slot_desc(dV, wg));
          wg_wait<0>();
          fence_regs(O);
          asm volatile("bar.sync %0, 128;" ::"r"(3 + wg) : "memory");
        }
        row_inv<false>(l0, l1, i0, i1, 0);
        store_o<0, 8>(O, i0, i1, qaddr);
        asm volatile("fence.proxy.async.shared::cta;" ::: "memory");
        asm volatile("bar.sync %0, 128;" ::"r"(3 + wg) : "memory");
        if (elect) {
          tma_store3(buf, &tmO, mp.qrow(t, wg));
          asm volatile("cp.async.bulk.commit_group;" ::: "memory");
          asm volatile("cp.async.bulk.wait_group 0;" ::: "memory");
        }
      }
    }
  }
}

typedef CUresult (*EncodeTiledFn)(CUtensorMap*, CUtensorMapDataType, cuuint32_t, void*, const cuuint64_t*, const cuuint64_t*,
                                  const cuuint32_t*, const cuuint32_t*, CUtensorMapInterleave, CUtensorMapSwizzle,
                                  CUtensorMapL2promotion, CUtensorMapFloatOOBfill);

void make_map(EncodeTiledFn fn, CUtensorMap* tm, const void* ptr, uint64_t rows, uint32_t box_rows) {
  cuuint64_t dims[3] = {64, rows, 2};
  cuuint64_t strides[2] = {256, 128};
  cuuint32_t box[3] = {64, box_rows, 2};
  cuuint32_t estr[3] = {1, 1, 1};
  fn(tm, CU_TENSOR_MAP_DATA_TYPE_BFLOAT16, 3, const_cast<void*>(ptr), dims, strides, box, estr, CU_TENSOR_MAP_INTERLEAVE_NONE,
     CU_TENSOR_MAP_SWIZZLE_128B, CU_TENSOR_MAP_L2_PROMOTION_L2_256B, CU_TENSOR_MAP_FLOAT_OOB_FILL_NONE);
}


}

extern "C" void kernel_launch(void* const* d_in, const int* in_sizes, int n_in, void* d_out, int out_size) {
  (void)in_sizes;
  (void)n_in;
  (void)out_size;
  static EncodeTiledFn fn = nullptr;
  if (!fn) {
    void* p = nullptr;
    cudaDriverEntryPointQueryResult qr;
    cudaGetDriverEntryPoint("cuTensorMapEncodeTiled", &p, cudaEnableDefault, &qr);
    fn = (EncodeTiledFn)p;
    cudaFuncSetAttribute(gqa_attn_kernel, cudaFuncAttributeMaxDynamicSharedMemorySize, SMEM_BYTES);
  }
  CUtensorMap tmQ, tmK, tmV, tmO;
  make_map(fn, &tmQ, d_in[0], (uint64_t)kBatch * kHq * kSeq, 64);
  make_map(fn, &tmK, d_in[1], (uint64_t)kBatch * kHkv * kSeq, 128);
  make_map(fn, &tmV, d_in[2], (uint64_t)kBatch * kHkv * kSeq, 128);
  make_map(fn, &tmO, d_out, (uint64_t)kBatch * kHq * kSeq, 64);
  gqa_attn_kernel<<<kNumCtas, 384, SMEM_BYTES>>>(tmQ, tmK, tmV, tmO, (const uint8_t*)d_in[0], (const uint8_t*)d_in[1], (const uint8_t*)d_in[2], (uint8_t*)d_out,
      (0x40000040ull << 32) | (1u << 16) | (SM_K >> 4), (0x40000040ull << 32) | (1024u << 16) | (SM_V >> 4));
}
```
